```python
import torch

def _softmax(x, axis=-1):
    return torch.softmax(x, dim=axis)
def _gelu(x):
    return torch.nn.functional.gelu(x, approximate="tanh")
def _silu(x):
    return torch.nn.functional.silu(x)
def _sigmoid(x):
    return torch.sigmoid(x)
def _layernorm(x, axis=-1, eps=1e-5):
    m = x.mean(dim=axis, keepdim=True)
    v = x.var(dim=axis, keepdim=True, unbiased=False)
    return (x - m) / torch.sqrt(v + eps)
def _scatter_add(tgt, idx, src, axis=0):
    return tgt.clone().index_add_(axis, idx, src)
def _segment_sum(src, seg, n):
    out = torch.zeros((n,) + src.shape[1:], dtype=src.dtype)
    return out.index_add_(0, seg, src)
def _pad(x, pw):
    flat = tuple(v for pair in reversed(pw) for v in pair)
    return torch.nn.functional.pad(x, flat)

kernel_name = 'interleave_layers__ssm_conv_h3__dense_activation_silu__prompt'

def setup_inputs():

    _w = (lambda a: (lambda t: t.to(torch.bfloat16) if t.is_floating_point() else t)(torch.as_tensor(a)))
    def _A_setup():
        B, S, D = 1, 2048, 448
        ks = 4
        return {
            "q": _w((lambda *s: torch.randn(*s, dtype=torch.bfloat16) * 0.05)(B, S, D)),
            "k": _w((lambda *s: torch.randn(*s, dtype=torch.bfloat16) * 0.2)(B, S, D)),
            "v": _w((lambda *s: torch.randn(*s, dtype=torch.bfloat16) * 0.2)(B, S, D)),
            "shift_k": _w((lambda *s: torch.randn(*s, dtype=torch.bfloat16) * 0.2)(D, ks) * 0.5),
            "ssm_k": _w((lambda *s: torch.randn(*s, dtype=torch.bfloat16) * 0.4)(D, S) * (1.0 / S ** 0.5)),
            "ssm_D": _w((lambda *s: torch.randn(*s, dtype=torch.bfloat16) * 0.2)(D)),
        }
    _A_in = _A_setup()

    def _B_setup():
        B, S, D, F = 1, 2048, 448, 1792
        return {
            "x": _w((lambda *s: torch.randn(*s, dtype=torch.bfloat16) * 0.05)(B, S, D)),
            "w1": _w((lambda *s: torch.randn(*s, dtype=torch.bfloat16) * 0.4)(D, F) * (D ** -0.5)),
            "w2": _w((lambda *s: torch.randn(*s, dtype=torch.bfloat16) * 0.1)(F, D) * (F ** -0.5)),
        }
    _B_in = _B_setup()

    return {
        "A_q": _A_in["q"],
        "A_k": _A_in["k"],
        "A_v": _A_in["v"],
        "A_shift_k": _A_in["shift_k"],
        "A_ssm_k": _A_in["ssm_k"],
        "A_ssm_D": _A_in["ssm_D"],
        "B_x": _B_in["x"],
        "B_w1": _B_in["w1"],
        "B_w2": _B_in["w2"],
    }

def reference(A_q, A_k, A_v, A_shift_k, A_ssm_k, A_ssm_D, B_x, B_w1, B_w2):
    def _A_ref(q, k, v, shift_k, ssm_k, ssm_D):
        B, S, D = q.shape
        ks = shift_k.shape[-1]
        k_pad = _pad(k, ((0, 0), (ks - 1, 0), (0, 0)))
        k_shift = torch.zeros_like(k)
        for t in range(ks):
            k_shift = k_shift + k_pad[:, t:t + S, :] * shift_k[:, ks - 1 - t][None, None, :]
        kv = k_shift * v
        L = 2 * S
        kv_pad = _pad(kv, ((0, 0), (0, S), (0, 0)))
        kf_pad = _pad(ssm_k, ((0, 0), (0, S)))
        kv_f = (lambda x, axes=(-2,-1): torch.fft.rfft2(x.float(), dim=axes))(kv_pad[:, None, :, :], axes=(1, 2))
        kf_f = (lambda x, axes=(-2,-1): torch.fft.rfft2(x.float(), dim=axes))(kf_pad[:, None, :], axes=(1, 2))
        kf_f = (lambda x, *d: x.permute(*d))(kf_f, 1, 2, 0)
        y_f = kv_f * kf_f[None, :, :, :]
        y = (lambda x, s, axes=(-2,-1): torch.fft.irfft2(x, s=s, dim=axes).to(torch.bfloat16))(y_f, (1, L), axes=(1, 2))[:, 0, :S, :]
        y = y + kv * ssm_D[None, None, :]
        return q * y

    def _B_ref(x, w1, w2):
        h = torch.einsum("bsd,df->bsf", x, w1)
        h = _silu(h)
        out = torch.einsum("bsf,fd->bsd", h, w2)
        return out

    x = A_q
    x = x + _A_ref(_layernorm(x, axis=-1), A_k, A_v, A_shift_k, A_ssm_k, A_ssm_D)
    x = x + _B_ref(_layernorm(x, axis=-1), B_w1, B_w2)
    x = x + _A_ref(_layernorm(x, axis=-1), A_k, A_v, A_shift_k, A_ssm_k, A_ssm_D)
    x = x + _B_ref(_layernorm(x, axis=-1), B_w1, B_w2)
    return x
```

```cpp
#include <cuda_runtime.h>
#include <cuda_bf16.h>
#include <cuda.h>
#include <stdint.h>

namespace {

constexpr int S_ = 2048, D_ = 448, F_ = 1792;
constexpr int NTHREADS = 384;
constexpr int REG_M = 224, REG_H = 56;
constexpr int XB = 2;
constexpr int KV_AHEAD = 3;
constexpr uint32_t SLOT = 28672;
constexpr uint32_t OFF_H = 7 * SLOT, OFF_BAR = 8 * SLOT + 1024, SMEM_TOTAL = OFF_BAR + 512;
constexpr uint32_t OFF_KV = 4 * SLOT, KV_HALF = 2176, KV_BLK = 2 * KV_HALF, KV_BYTES = 2 * 132 * 16;
constexpr uint32_t OFF_SSM = OFF_KV + 8 * KV_BLK, SSM_PL = 2112, SSM_CH = 2 * SSM_PL;
constexpr uint32_t OFF_TAB = OFF_SSM + 4 * SSM_CH, TAB_PL = 8320;
static_assert(OFF_TAB + 4 * TAB_PL <= OFF_H, "conv scratch overflow");
constexpr uint32_t STG_PITCH = 944, STG_TILE = 14720;
enum { B_TAB = 0, B_WFULL = 16, B_Q = 23, B_WEMPTY = 24, B_CFREE1 = 31, B_KV = 32, B_HFULL = 40, B_HFREE = 44,
       B_CFREE0 = 46, B_HCONS = 47 };

__device__ uint4 g_Y[1024 * 112 * 2];
__device__ uint4 g_X[16 * 2 * 8 * 512];
__device__ uint4 g_P[16 * 2 * 8 * 4 * 512];
__device__ uint4 g_St[128 * 2 * 2 * 512];
__device__ unsigned g_epoch[128];
#define TS(i) do {} while (0)
#define STALL(c, stmt) do { stmt; } while (0)
#define GT(i) do {} while (0)

__device__ __forceinline__ void mbar_init(uint32_t b, uint32_t c) { asm volatile("mbarrier.init.shared::cta.b64 [%0], %1;" ::"r"(b), "r"(c) : "memory"); }
__device__ __forceinline__ void mbar_expect(uint32_t b, uint32_t bytes) { asm volatile("mbarrier.arrive.expect_tx.shared::cta.b64 _, [%0], %1;" ::"r"(b), "r"(bytes) : "memory"); }
__device__ __forceinline__ void mbar_arrive(uint32_t b) { asm volatile("mbarrier.arrive.shared::cta.b64 _, [%0];" ::"r"(b) : "memory"); }
__device__ __forceinline__ void mbar_arrive_remote(uint32_t b) { asm volatile("mbarrier.arrive.shared::cluster.b64 _, [%0];" ::"r"(b) : "memory"); }
__device__ __forceinline__ void mbar_wait_b(uint32_t b, uint32_t parity, int& budget) {
  uint32_t ok;
  do {
    asm volatile("{.reg .pred p; mbarrier.try_wait.parity.shared::cta.b64 p, [%1], %2; selp.u32 %0, 1, 0, p;}" : "=r"(ok) : "r"(b), "r"(parity) : "memory");
  } while (!ok && --budget > 0);
}
#define mbar_wait(b, parity) mbar_wait_b(b, parity, budget)
__device__ __forceinline__ void warp_arrive(uint32_t b, int lane) { __syncwarp(); if (lane == 0) mbar_arrive(b); }
__device__ __forceinline__ uint32_t mapa(uint32_t a, uint32_t r) { uint32_t o; asm("mapa.shared::cluster.u32 %0, %1, %2;" : "=r"(o) : "r"(a), "r"(r)); return o; }
__device__ __forceinline__ void tma2(const CUtensorMap* m, uint32_t dst, uint32_t bar, int x, int y) {
  asm volatile("cp.async.bulk.tensor.2d.shared::cluster.global.mbarrier::complete_tx::bytes [%0], [%1, {%3, %4}], [%2];" ::"r"(dst), "l"(m), "r"(bar), "r"(x), "r"(y) : "memory");
}
__device__ __forceinline__ void tma3(const CUtensorMap* m, uint32_t dst, uint32_t bar, int x, int y, int z) {
  asm volatile("cp.async.bulk.tensor.3d.shared::cluster.global.mbarrier::complete_tx::bytes [%0], [%1, {%3, %4, %5}], [%2];" ::"r"(dst), "l"(m), "r"(bar), "r"(x), "r"(y), "r"(z) : "memory");
}
__device__ __forceinline__ void bulk_g2s(uint32_t dst, const void* src, uint32_t bytes, uint32_t bar) {
  asm volatile("cp.async.bulk.shared::cluster.global.mbarrier::complete_tx::bytes [%0], [%1], %2, [%3];" ::"r"(dst), "l"(src), "r"(bytes), "r"(bar) : "memory");
}
__device__ __forceinline__ void ll_ld(uint32_t* v, const uint4* p) {
  asm volatile("{.reg .b128 x; ld.relaxed.gpu.global.b128 x, [%4]; mov.b128 {%0,%1,%2,%3}, x;}" : "=r"(v[0]), "=r"(v[1]), "=r"(v[2]), "=r"(v[3]) : "l"(p) : "memory");
}
__device__ __forceinline__ void ll_st(uint4* p, uint32_t a, uint32_t b, uint32_t c, uint32_t d) {
  asm volatile("{.reg .b128 x; mov.b128 x, {%1,%2,%3,%4}; st.relaxed.gpu.global.b128 [%0], x;}" ::"l"(p), "r"(a), "r"(b), "r"(c), "r"(d) : "memory");
}
__device__ __forceinline__ uint32_t lds32(uint32_t a) { uint32_t v; asm volatile("ld.shared.u32 %0, [%1];" : "=r"(v) : "r"(a) : "memory"); return v; }
__device__ __forceinline__ uint32_t lds16(uint32_t a) { uint32_t v; asm volatile("ld.shared.u16 %0, [%1];" : "=r"(v) : "r"(a) : "memory"); return v; }
__device__ __forceinline__ void lds128(uint32_t* v, uint32_t a) { asm volatile("ld.shared.v4.u32 {%0,%1,%2,%3}, [%4];" : "=r"(v[0]), "=r"(v[1]), "=r"(v[2]), "=r"(v[3]) : "r"(a) : "memory"); }
__device__ __forceinline__ void sts32(uint32_t a, uint32_t v) { asm volatile("st.shared.u32 [%0], %1;" ::"r"(a), "r"(v) : "memory"); }
__device__ __forceinline__ void sts16(uint32_t a, uint32_t v) { asm volatile("st.shared.u16 [%0], %1;" ::"r"(a), "r"(v) : "memory"); }
__device__ __forceinline__ void sts64(uint32_t a, uint32_t v0, uint32_t v1) { asm volatile("st.shared.v2.u32 [%0], {%1,%2};" ::"r"(a), "r"(v0), "r"(v1) : "memory"); }
__device__ __forceinline__ uint32_t prmt(uint32_t a, uint32_t b, uint32_t s) { uint32_t o; asm("prmt.b32 %0, %1, %2, %3;" : "=r"(o) : "r"(a), "r"(b), "r"(s)); return o; }
__device__ __forceinline__ uint32_t pack2(float lo, float hi) { uint32_t o; asm("cvt.rn.bf16x2.f32 %0, %1, %2;" : "=r"(o) : "f"(hi), "f"(lo)); return o; }
__device__ __forceinline__ uint32_t bmul2(uint32_t a, uint32_t b) { uint32_t o; asm("mul.rn.bf16x2 %0, %1, %2;" : "=r"(o) : "r"(a), "r"(b)); return o; }
__device__ __forceinline__ uint32_t badd2(uint32_t a, uint32_t b) { uint32_t o; asm("add.rn.bf16x2 %0, %1, %2;" : "=r"(o) : "r"(a), "r"(b)); return o; }
__device__ __forceinline__ float blo(uint32_t w) { return __uint_as_float(w << 16); }
__device__ __forceinline__ float bhi(uint32_t w) { return __uint_as_float(w & 0xFFFF0000u); }
__device__ __forceinline__ uint32_t desc_lo(uint32_t addr, uint32_t lbo) { return ((addr & 0x3FFFF) >> 4) | ((lbo >> 4) << 16); }
constexpr uint32_t HI_NONE = 128 >> 4, HI_128 = (1024 >> 4) | (1u << 30), HI_64 = (512 >> 4) | (2u << 30);
__device__ __forceinline__ bool elect() {
  uint32_t p;
  asm volatile("{.reg .pred P; elect.sync _|P, 0xffffffff; selp.u32 %0, 1, 0, P;}" : "=r"(p));
  return p;
}
#define WG_FENCE() asm volatile("wgmma.fence.sync.aligned;" ::: "memory")
#define WG_COMMIT() asm volatile("wgmma.commit_group.sync.aligned;" ::: "memory")
#define WG_WAIT(n) asm volatile("wgmma.wait_group.sync.aligned %0;" ::"n"(n) : "memory")
template <int N> __device__ __forceinline__ void pin(float* d) {
#pragma unroll
  for (int i = 0; i < N; i++) asm volatile("" : "+f"(d[i])::"memory");
}
__device__ __forceinline__ void turn_wait(int id) { asm volatile("bar.sync %0, 256;" ::"r"(id) : "memory"); }
__device__ __forceinline__ void turn_give(int id) { asm volatile("bar.arrive %0, 256;" ::"r"(id) : "memory"); }

template <int TB, uint32_t HI> __device__ __forceinline__ void wg_rs_8(float* d, const uint32_t* a, uint32_t db, int sd) {
  asm volatile("{.reg .pred p; .reg .b64 dd; setp.ne.b32 p, %9, 0; mov.b64 dd, {%8, %11}; wgmma.mma_async.sync.aligned.m64n8k16.f32.bf16.bf16 "
    "{%0,%1,%2,%3}, "
    "{%4,%5,%6,%7}, dd, p, 1, 1, %10;}"
    : "+f"(d[0]), "+f"(d[1]), "+f"(d[2]), "+f"(d[3])
    : "r"(a[0]), "r"(a[1]), "r"(a[2]), "r"(a[3]), "r"(db), "r"(sd), "n"(TB), "n"(HI));
}
template <int TB, uint32_t HI> __device__ __forceinline__ void wg_rs_16(float* d, const uint32_t* a, uint32_t db, int sd) {
  asm volatile("{.reg .pred p; .reg .b64 dd; setp.ne.b32 p, %13, 0; mov.b64 dd, {%12, %15}; wgmma.mma_async.sync.aligned.m64n16k16.f32.bf16.bf16 "
    "{%0,%1,%2,%3,%4,%5,%6,%7}, "
    "{%8,%9,%10,%11}, dd, p, 1, 1, %14;}"
    : "+f"(d[0]), "+f"(d[1]), "+f"(d[2]), "+f"(d[3]), "+f"(d[4]), "+f"(d[5]), "+f"(d[6]), "+f"(d[7])
    : "r"(a[0]), "r"(a[1]), "r"(a[2]), "r"(a[3]), "r"(db), "r"(sd), "n"(TB), "n"(HI));
}
template <int TB, uint32_t HI> __device__ __forceinline__ void wg_rs_24(float* d, const uint32_t* a, uint32_t db, int sd) {
  asm volatile("{.reg .pred p; .reg .b64 dd; setp.ne.b32 p, %17, 0; mov.b64 dd, {%16, %19}; wgmma.mma_async.sync.aligned.m64n24k16.f32.bf16.bf16 "
    "{%0,%1,%2,%3,%4,%5,%6,%7,%8,%9,%10,%11}, "
    "{%12,%13,%14,%15}, dd, p, 1, 1, %18;}"
    : "+f"(d[0]), "+f"(d[1]), "+f"(d[2]), "+f"(d[3]), "+f"(d[4]), "+f"(d[5]), "+f"(d[6]), "+f"(d[7]), "+f"(d[8]), "+f"(d[9]), "+f"(d[10]), "+f"(d[11])
    : "r"(a[0]), "r"(a[1]), "r"(a[2]), "r"(a[3]), "r"(db), "r"(sd), "n"(TB), "n"(HI));
}
template <int TB, uint32_t HI> __device__ __forceinline__ void wg_rs_32(float* d, const uint32_t* a, uint32_t db, int sd) {
  asm volatile("{.reg .pred p; .reg .b64 dd; setp.ne.b32 p, %21, 0; mov.b64 dd, {%20, %23}; wgmma.mma_async.sync.aligned.m64n32k16.f32.bf16.bf16 "
    "{%0,%1,%2,%3,%4,%5,%6,%7,%8,%9,%10,%11,%12,%13,%14,%15}, "
    "{%16,%17,%18,%19}, dd, p, 1, 1, %22;}"
    : "+f"(d[0]), "+f"(d[1]), "+f"(d[2]), "+f"(d[3]), "+f"(d[4]), "+f"(d[5]), "+f"(d[6]), "+f"(d[7]), "+f"(d[8]), "+f"(d[9]), "+f"(d[10]), "+f"(d[11]),
      "+f"(d[12]), "+f"(d[13]), "+f"(d[14]), "+f"(d[15])
    : "r"(a[0]), "r"(a[1]), "r"(a[2]), "r"(a[3]), "r"(db), "r"(sd), "n"(TB), "n"(HI));
}
template <int TB, uint32_t HI> __device__ __forceinline__ void wg_rs_40(float* d, const uint32_t* a, uint32_t db, int sd) {
  asm volatile("{.reg .pred p; .reg .b64 dd; setp.ne.b32 p, %25, 0; mov.b64 dd, {%24, %27}; wgmma.mma_async.sync.aligned.m64n40k16.f32.bf16.bf16 "
    "{%0,%1,%2,%3,%4,%5,%6,%7,%8,%9,%10,%11,%12,%13,%14,%15,%16,%17,%18,%19}, "
    "{%20,%21,%22,%23}, dd, p, 1, 1, %26;}"
    : "+f"(d[0]), "+f"(d[1]), "+f"(d[2]), "+f"(d[3]), "+f"(d[4]), "+f"(d[5]), "+f"(d[6]), "+f"(d[7]), "+f"(d[8]), "+f"(d[9]), "+f"(d[10]), "+f"(d[11]),
      "+f"(d[12]), "+f"(d[13]), "+f"(d[14]), "+f"(d[15]), "+f"(d[16]), "+f"(d[17]), "+f"(d[18]), "+f"(d[19])
    : "r"(a[0]), "r"(a[1]), "r"(a[2]), "r"(a[3]), "r"(db), "r"(sd), "n"(TB), "n"(HI));
}
template <int TB, uint32_t HI> __device__ __forceinline__ void wg_rs_48(float* d, const uint32_t* a, uint32_t db, int sd) {
  asm volatile("{.reg .pred p; .reg .b64 dd; setp.ne.b32 p, %29, 0; mov.b64 dd, {%28, %31}; wgmma.mma_async.sync.aligned.m64n48k16.f32.bf16.bf16 "
    "{%0,%1,%2,%3,%4,%5,%6,%7,%8,%9,%10,%11,%12,%13,%14,%15,%16,%17,%18,%19,%20,%21,%22,%23}, "
    "{%24,%25,%26,%27}, dd, p, 1, 1, %30;}"
    : "+f"(d[0]), "+f"(d[1]), "+f"(d[2]), "+f"(d[3]), "+f"(d[4]), "+f"(d[5]), "+f"(d[6]), "+f"(d[7]), "+f"(d[8]), "+f"(d[9]), "+f"(d[10]), "+f"(d[11]),
      "+f"(d[12]), "+f"(d[13]), "+f"(d[14]), "+f"(d[15]), "+f"(d[16]), "+f"(d[17]), "+f"(d[18]), "+f"(d[19]), "+f"(d[20]), "+f"(d[21]), "+f"(d[22]), "+f"(d[23])
    : "r"(a[0]), "r"(a[1]), "r"(a[2]), "r"(a[3]), "r"(db), "r"(sd), "n"(TB), "n"(HI));
}
template <int TB, uint32_t HI> __device__ __forceinline__ void wg_rs_56(float* d, const uint32_t* a, uint32_t db, int sd) {
  asm volatile("{.reg .pred p; .reg .b64 dd; setp.ne.b32 p, %33, 0; mov.b64 dd, {%32, %35}; wgmma.mma_async.sync.aligned.m64n56k16.f32.bf16.bf16 "
    "{%0,%1,%2,%3,%4,%5,%6,%7,%8,%9,%10,%11,%12,%13,%14,%15,%16,%17,%18,%19,%20,%21,%22,%23,%24,%25,%26,%27}, "
    "{%28,%29,%30,%31}, dd, p, 1, 1, %34;}"
    : "+f"(d[0]), "+f"(d[1]), "+f"(d[2]), "+f"(d[3]), "+f"(d[4]), "+f"(d[5]), "+f"(d[6]), "+f"(d[7]), "+f"(d[8]), "+f"(d[9]), "+f"(d[10]), "+f"(d[11]),
      "+f"(d[12]), "+f"(d[13]), "+f"(d[14]), "+f"(d[15]), "+f"(d[16]), "+f"(d[17]), "+f"(d[18]), "+f"(d[19]), "+f"(d[20]), "+f"(d[21]), "+f"(d[22]), "+f"(d[23]),
      "+f"(d[24]), "+f"(d[25]), "+f"(d[26]), "+f"(d[27])
    : "r"(a[0]), "r"(a[1]), "r"(a[2]), "r"(a[3]), "r"(db), "r"(sd), "n"(TB), "n"(HI));
}
template <int TB, uint32_t HI> __device__ __forceinline__ void wg_rs_64(float* d, const uint32_t* a, uint32_t db, int sd) {
  asm volatile("{.reg .pred p; .reg .b64 dd; setp.ne.b32 p, %37, 0; mov.b64 dd, {%36, %39}; wgmma.mma_async.sync.aligned.m64n64k16.f32.bf16.bf16 "
    "{%0,%1,%2,%3,%4,%5,%6,%7,%8,%9,%10,%11,%12,%13,%14,%15,%16,%17,%18,%19,%20,%21,%22,%23,%24,%25,%26,%27,%28,%29,%30,%31}, "
    "{%32,%33,%34,%35}, dd, p, 1, 1, %38;}"
    : "+f"(d[0]), "+f"(d[1]), "+f"(d[2]), "+f"(d[3]), "+f"(d[4]), "+f"(d[5]), "+f"(d[6]), "+f"(d[7]), "+f"(d[8]), "+f"(d[9]), "+f"(d[10]), "+f"(d[11]),
      "+f"(d[12]), "+f"(d[13]), "+f"(d[14]), "+f"(d[15]), "+f"(d[16]), "+f"(d[17]), "+f"(d[18]), "+f"(d[19]), "+f"(d[20]), "+f"(d[21]), "+f"(d[22]), "+f"(d[23]),
      "+f"(d[24]), "+f"(d[25]), "+f"(d[26]), "+f"(d[27]), "+f"(d[28]), "+f"(d[29]), "+f"(d[30]), "+f"(d[31])
    : "r"(a[0]), "r"(a[1]), "r"(a[2]), "r"(a[3]), "r"(db), "r"(sd), "n"(TB), "n"(HI));
}
template <int TB, uint32_t HI> __device__ __forceinline__ void wg_rs_72(float* d, const uint32_t* a, uint32_t db, int sd) {
  asm volatile("{.reg .pred p; .reg .b64 dd; setp.ne.b32 p, %41, 0; mov.b64 dd, {%40, %43}; wgmma.mma_async.sync.aligned.m64n72k16.f32.bf16.bf16 "
    "{%0,%1,%2,%3,%4,%5,%6,%7,%8,%9,%10,%11,%12,%13,%14,%15,%16,%17,%18,%19,%20,%21,%22,%23,%24,%25,%26,%27,%28,%29,%30,%31,%32,%33,%34,%35}, "
    "{%36,%37,%38,%39}, dd, p, 1, 1, %42;}"
    : "+f"(d[0]), "+f"(d[1]), "+f"(d[2]), "+f"(d[3]), "+f"(d[4]), "+f"(d[5]), "+f"(d[6]), "+f"(d[7]), "+f"(d[8]), "+f"(d[9]), "+f"(d[10]), "+f"(d[11]),
      "+f"(d[12]), "+f"(d[13]), "+f"(d[14]), "+f"(d[15]), "+f"(d[16]), "+f"(d[17]), "+f"(d[18]), "+f"(d[19]), "+f"(d[20]), "+f"(d[21]), "+f"(d[22]), "+f"(d[23]),
      "+f"(d[24]), "+f"(d[25]), "+f"(d[26]), "+f"(d[27]), "+f"(d[28]), "+f"(d[29]), "+f"(d[30]), "+f"(d[31]), "+f"(d[32]), "+f"(d[33]), "+f"(d[34]), "+f"(d[35])
    : "r"(a[0]), "r"(a[1]), "r"(a[2]), "r"(a[3]), "r"(db), "r"(sd), "n"(TB), "n"(HI));
}
template <int TB, uint32_t HI> __device__ __forceinline__ void wg_rs_192(float* d, const uint32_t* a, uint32_t db, int sd) {
  asm volatile("{.reg .pred p; .reg .b64 dd; setp.ne.b32 p, %101, 0; mov.b64 dd, {%100, %103}; wgmma.mma_async.sync.aligned.m64n192k16.f32.bf16.bf16 "
    "{%0,%1,%2,%3,%4,%5,%6,%7,%8,%9,%10,%11,%12,%13,%14,%15,%16,%17,%18,%19,%20,%21,%22,%23,%24,%25,%26,%27,%28,%29,%30,%31,%32,%33,%34,%35,%36,%37,%38,%39,%40,%41,%42,%43,%44,%45,%46,%47,%48,%49,%50,%51,%52,%53,%54,%55,%56,%57,%58,%59,%60,%61,%62,%63,%64,%65,%66,%67,%68,%69,%70,%71,%72,%73,%74,%75,%76,%77,%78,%79,%80,%81,%82,%83,%84,%85,%86,%87,%88,%89,%90,%91,%92,%93,%94,%95}, "
    "{%96,%97,%98,%99}, dd, p, 1, 1, %102;}"
    : "+f"(d[0]), "+f"(d[1]), "+f"(d[2]), "+f"(d[3]), "+f"(d[4]), "+f"(d[5]), "+f"(d[6]), "+f"(d[7]), "+f"(d[8]), "+f"(d[9]), "+f"(d[10]), "+f"(d[11]),
      "+f"(d[12]), "+f"(d[13]), "+f"(d[14]), "+f"(d[15]), "+f"(d[16]), "+f"(d[17]), "+f"(d[18]), "+f"(d[19]), "+f"(d[20]), "+f"(d[21]), "+f"(d[22]), "+f"(d[23]),
      "+f"(d[24]), "+f"(d[25]), "+f"(d[26]), "+f"(d[27]), "+f"(d[28]), "+f"(d[29]), "+f"(d[30]), "+f"(d[31]), "+f"(d[32]), "+f"(d[33]), "+f"(d[34]), "+f"(d[35]),
      "+f"(d[36]), "+f"(d[37]), "+f"(d[38]), "+f"(d[39]), "+f"(d[40]), "+f"(d[41]), "+f"(d[42]), "+f"(d[43]), "+f"(d[44]), "+f"(d[45]), "+f"(d[46]), "+f"(d[47]),
      "+f"(d[48]), "+f"(d[49]), "+f"(d[50]), "+f"(d[51]), "+f"(d[52]), "+f"(d[53]), "+f"(d[54]), "+f"(d[55]), "+f"(d[56]), "+f"(d[57]), "+f"(d[58]), "+f"(d[59]),
      "+f"(d[60]), "+f"(d[61]), "+f"(d[62]), "+f"(d[63]), "+f"(d[64]), "+f"(d[65]), "+f"(d[66]), "+f"(d[67]), "+f"(d[68]), "+f"(d[69]), "+f"(d[70]), "+f"(d[71]),
      "+f"(d[72]), "+f"(d[73]), "+f"(d[74]), "+f"(d[75]), "+f"(d[76]), "+f"(d[77]), "+f"(d[78]), "+f"(d[79]), "+f"(d[80]), "+f"(d[81]), "+f"(d[82]), "+f"(d[83]),
      "+f"(d[84]), "+f"(d[85]), "+f"(d[86]), "+f"(d[87]), "+f"(d[88]), "+f"(d[89]), "+f"(d[90]), "+f"(d[91]), "+f"(d[92]), "+f"(d[93]), "+f"(d[94]), "+f"(d[95])
    : "r"(a[0]), "r"(a[1]), "r"(a[2]), "r"(a[3]), "r"(db), "r"(sd), "n"(TB), "n"(HI));
}
template <int N, int TB, uint32_t HI> __device__ __forceinline__ void wg_rs(float* d, const uint32_t* a, uint32_t db, int sd) {
  if constexpr (N == 8) wg_rs_8<TB, HI>(d, a, db, sd);
  if constexpr (N == 16) wg_rs_16<TB, HI>(d, a, db, sd);
  if constexpr (N == 24) wg_rs_24<TB, HI>(d, a, db, sd);
  if constexpr (N == 32) wg_rs_32<TB, HI>(d, a, db, sd);
  if constexpr (N == 40) wg_rs_40<TB, HI>(d, a, db, sd);
  if constexpr (N == 48) wg_rs_48<TB, HI>(d, a, db, sd);
  if constexpr (N == 56) wg_rs_56<TB, HI>(d, a, db, sd);
  if constexpr (N == 64) wg_rs_64<TB, HI>(d, a, db, sd);
  if constexpr (N == 72) wg_rs_72<TB, HI>(d, a, db, sd);
  if constexpr (N == 192) wg_rs_192<TB, HI>(d, a, db, sd);
}

struct ConvCarry { float hi1[4], a[4], b[4]; };

template <int I>
__device__ __forceinline__ void conv_fold(float (&acc)[4][36], ConvCarry& cy, float* o, int src1, int src2, bool t3, bool g2) {
#pragma unroll
  for (int ch = 0; ch < 4; ch++) {
    float* d = acc[ch] + 4 * (7 - I);
    pin<4>(d);
    float snd = (I >= 0 && t3) ? cy.hi1[ch] : d[2];
    cy.hi1[ch] = d[2];
    float s0 = d[1] + __shfl_sync(0xffffffffu, snd, src1);
    float s1 = d[0] + d[3];
    float a = g2 ? s0 : s1, b = g2 ? s1 : s0;
    if (I >= 0) {
      bool p3 = t3 && g2;
      float sa = p3 ? cy.a[ch] : a, sb = p3 ? cy.b[ch] : b;
      o[ch] = sb + __shfl_sync(0xffffffffu, sa, src2);
    }
    cy.a[ch] = a;
    cy.b[ch] = b;
  }
}

__device__ __forceinline__ float row_sum(float a) {
#pragma unroll
  for (int k = 0; k < 4; k++) a += __shfl_xor_sync(0xffffffffu, a, k < 2 ? (1 << k) : (2 << k));
  return a;
}
__device__ __forceinline__ void row_sum2(float& a, float& b) {
#pragma unroll
  for (int k = 0; k < 4; k++) {
    const int x = k < 2 ? (1 << k) : (2 << k);
    const float ao = __shfl_xor_sync(0xffffffffu, a, x), bo = __shfl_xor_sync(0xffffffffu, b, x);
    a += ao;
    b += bo;
  }
}
template <int N> __device__ __forceinline__ float tree_sum(const float* v) {
  if constexpr (N == 1) return v[0];
  else return tree_sum<N / 2>(v) + tree_sum<N - N / 2>(v + N / 2);
}
template <int N> __device__ __forceinline__ void acc_moments(const float* v, float* s1, float* s2) {
#pragma unroll
  for (int i = 0; i < N; i++) { s1[i & 3] += v[i]; s2[i & 3] = fmaf(v[i], v[i], s2[i & 3]); }
}
__device__ __forceinline__ void finish_moments(const float* s1, const float* s2, float& mean, float& rstd) {
  float a = (s1[0] + s1[1]) + (s1[2] + s1[3]), b = (s2[0] + s2[1]) + (s2[2] + s2[3]);
  row_sum2(a, b);
  mean = a * (1.f / 448.f);
  const float var = fmaxf(fmaf(b, 1.f / 448.f, -mean * mean), 0.f);
  asm("rsqrt.approx.ftz.f32 %0, %1;" : "=f"(rstd) : "f"(var + 1e-5f));
}

template <int N> __device__ __forceinline__ bool ll_bad(uint32_t (*v)[4], uint32_t tag) {
  uint32_t x = 0;
#pragma unroll
  for (int i = 0; i < N; i++) x |= v[i][3] ^ tag;
  return __any_sync(0xffffffffu, x > 0xFFFFu);
}

__global__ void __cluster_dims__(2, 1, 1) __launch_bounds__(NTHREADS, 1)
h3ffn_kernel(const __grid_constant__ CUtensorMap tmK, const __grid_constant__ CUtensorMap tmV,
             const __grid_constant__ CUtensorMap tmW1m, const __grid_constant__ CUtensorMap tmW1t,
             const __grid_constant__ CUtensorMap tmW2m, const __grid_constant__ CUtensorMap tmW2t,
             const __nv_bfloat16* __restrict__ q, const __nv_bfloat16* __restrict__ shiftk,
             const __nv_bfloat16* __restrict__ ssmk, const __nv_bfloat16* __restrict__ ssmD,
             const __nv_bfloat16* __restrict__ w1, const __nv_bfloat16* __restrict__ w2, __nv_bfloat16* __restrict__ out,
             const uint32_t zero) {
  extern __shared__ __align__(1024) unsigned char smem_raw[];
  const uint32_t sb = (uint32_t)__cvta_generic_to_shared(smem_raw);
  const uint32_t bars = sb + OFF_BAR;
  const int tid = threadIdx.x, lane = tid & 31;
  const int warp = __shfl_sync(0xffffffffu, tid >> 5, 0), wg = warp >> 2;
  const int cl = blockIdx.x >> 1, r = blockIdx.x & 1;
  int gpc, idx;
  if (cl < 4) { gpc = 0; idx = 4 + cl; }
  else if (cl < 36) { gpc = (cl - 4) & 7; idx = (cl - 4) >> 3; }
  else { gpc = 1 + (cl - 36) % 7; idx = 4 + (cl - 36) / 7; }
  const int ps = gpc >> 1, gi = (gpc & 1) * 8 + idx;
  const bool conv = idx < 7;
  const int cc = idx * 8 + gpc, quad = 2 * cc + r;
  const int own = gi * 8 + 2 * ps + r;
  int budget = 1 << 18;

  if (tid == 128) { GT(62); TS(56); }
  if (wg == 2) {
    const int ht = tid - 256, wv = warp - 8;
    uint4 skw[4];
    if (conv) {
#pragma unroll
      for (int p = 0; p < 4; p++) skw[p] = __ldg(reinterpret_cast<const uint4*>(shiftk + cc * 32) + p);
    }
    auto kv_load = [&](int i) {
      const uint32_t b = bars + 8 * (B_KV + i), dst = sb + OFF_KV + i * KV_BLK;
      tma2(&tmK, dst, b, cc * 8, (2 * i + r) * 128 - 4);
      tma2(&tmV, dst + KV_HALF, b, cc * 8, (2 * i + r) * 128 - 4);
    };
    if (elect()) {
      mbar_init(bars + 8 * (B_KV + wv), 1);
      mbar_expect(bars + 8 * (B_KV + wv), KV_BYTES);
      if (conv && wv < KV_AHEAD) kv_load(wv);
      mbar_init(bars + 8 * (B_KV + 4 + wv), 1);
      mbar_init(bars + 8 * (B_HFULL + wv), 1);
      mbar_init(bars + 8 * (B_HFREE + wv), 4);
      mbar_expect(bars + 8 * (B_KV + 4 + wv), KV_BYTES);
      mbar_expect(bars + 8 * (B_HFULL + wv), SLOT);
      asm volatile("fence.mbarrier_init.release.cluster;" ::: "memory");
    }
    __syncwarp();
    if (ht == 0) TS(57);
    asm volatile("barrier.cluster.arrive.relaxed.aligned;" ::: "memory");
    asm volatile("setmaxnreg.dec.sync.aligned.u32 %0;" ::"n"(REG_H));
    if (conv) {
      uint32_t sk[4][4];
#pragma unroll
      for (int p = 0; p < 4; p++) {
        sk[0][p] = prmt(skw[p].x, skw[p].z, 0x5410); sk[1][p] = prmt(skw[p].x, skw[p].z, 0x7632);
        sk[2][p] = prmt(skw[p].y, skw[p].w, 0x5410); sk[3][p] = prmt(skw[p].y, skw[p].w, 0x7632);
      }
      asm volatile("barrier.cluster.wait.aligned;" ::: "memory");
      if (ht == 0) TS(47);
      const uint32_t tloc = sb + OFF_TAB + 128 + 4 * (ht ^ ((ht >> 1) & 16)) + 512 * r;
      const int y4 = 32 * wv + 4 * (lane & 7);
      const uint32_t trem = mapa(sb + OFF_TAB + (lane >> 3) * TAB_PL + 128 + 4 * (y4 ^ ((y4 >> 1) & 16)) + 512 * r, r ^ 1);
      const uint32_t brem = mapa(bars + 8 * (B_TAB + r), r ^ 1);
      const uint32_t xst = sb + OFF_H + STG_TILE + 7168 + wv * 512;
#pragma unroll 1
      for (int i = 0; i < 8; i++) {
        mbar_wait(bars + 8 * (B_KV + i), 0);
        if (ht == 0) TS(48 + i);
        if (i + KV_AHEAD < 8 && wv == (i & 3) && elect()) kv_load(i + KV_AHEAD);
        const uint32_t ka = sb + OFF_KV + i * KV_BLK + ht * 16;
        uint32_t a[2][4];
#pragma unroll
        for (int d = 0; d < 5; d++) {
          uint32_t kr[4];
          lds128(kr, ka + d * 16);
#pragma unroll
          for (int p = 0; p < 4; p++) {
            if (d < 4) a[0][p] = d == 0 ? bmul2(kr[p], sk[3][p]) : badd2(a[0][p], bmul2(kr[p], sk[3 - d][p]));
            if (d > 0) a[1][p] = d == 1 ? bmul2(kr[p], sk[3][p]) : badd2(a[1][p], bmul2(kr[p], sk[4 - d][p]));
          }
        }
#pragma unroll
        for (int d = 0; d < 2; d++) {
          uint32_t vr[4];
          lds128(vr, ka + KV_HALF + (3 + d) * 16);
#pragma unroll
          for (int p = 0; p < 4; p++) a[d][p] = bmul2(a[d][p], vr[p]);
        }
#pragma unroll
        for (int p = 0; p < 2; p++) {
          const uint32_t o1 = r ? a[1][p] : a[1][2 + p], o0 = r ? a[0][p] : a[0][2 + p];
          const uint32_t m1 = r ? a[1][2 + p] : a[1][p], m0 = r ? a[0][2 + p] : a[0][p];
#pragma unroll
          for (int e = 0; e < 2; e++) {
            sts32(xst + (2 * p + e) * 128 + lane * 4, prmt(o1, o0, e ? 0x7632 : 0x5410));
            sts32(tloc + (2 * p + e) * TAB_PL + i * 1024, prmt(m1, m0, e ? 0x7632 : 0x5410));
          }
        }
        warp_arrive(bars + 8 * (B_TAB + 2 * i + r), lane);
        uint32_t x4[4];
        lds128(x4, xst + lane * 16);
        asm volatile("st.async.shared::cluster.mbarrier::complete_tx::bytes.v4.u32 [%0], {%1,%2,%3,%4}, [%5];" ::"r"(trem + i * 1024),
                     "r"(x4[0]), "r"(x4[1]), "r"(x4[2]), "r"(x4[3]), "r"(brem + 16 * i) : "memory");
        __syncwarp();
        if (i == 4 && elect()) {
          if (wv < 2) bulk_g2s(sb + OFF_H + wv * STG_TILE, q + (size_t)(wv * 1024 + own * 8) * D_, 7168, bars + 8 * B_Q);
          else asm volatile("cp.async.bulk.prefetch.L2.global [%0], %1;" ::"l"((wv == 2 ? w1 : w2) + (size_t)blockIdx.x * 6272), "r"(12544) : "memory");
        }
      }
      warp_arrive(bars + 8 * B_CFREE0, lane);
    } else {
      asm volatile("barrier.cluster.wait.aligned;" ::: "memory");
      if (elect()) {
        if (wv < 2) bulk_g2s(sb + OFF_H + wv * STG_TILE, q + (size_t)(wv * 1024 + own * 8) * D_, 7168, bars + 8 * B_Q);
        else asm volatile("cp.async.bulk.prefetch.L2.global [%0], %1;" ::"l"((wv == 2 ? w1 : w2) + (size_t)blockIdx.x * 6272), "r"(12544) : "memory");
      }
    }
    if (ht == 0) TS(32);
    if (elect()) {
#pragma unroll 1
      for (int ph = 0; ph < 4; ph++) {
#pragma unroll 1
        for (int j = wv; j < 7; j += 4) {
          if (ph > 0) mbar_wait(bars + 8 * (B_WEMPTY + j), (ph - 1) & 1);
          else if (conv && j >= 4) mbar_wait(bars + 8 * (j == 4 ? B_CFREE0 : B_CFREE1), 0);
          const uint32_t b = bars + 8 * (B_WFULL + j), dst = sb + j * SLOT;
          mbar_expect(b, SLOT);
          if (!(ph & 1)) {
#pragma unroll
            for (int h = 0; h < 2; h++) {
              const int hs = 2 * j + h;
              const int row = hs < 7 ? 32 * hs : (hs < 13 ? 32 * hs + 32 : 224);
              tma3(&tmW1m, dst + h * 14336, b, 0, row, 7 * ps + 4 * r);
              tma2(&tmW1t, dst + h * 14336 + 12288, b, 448 * ps + 192 + 32 * r, row);
            }
          } else if (j < 6) {
            tma2(&tmW2m, dst, b, 256 * r + 64 * (j >> 1), 448 * ps + 224 * ((j & 1) ^ r));
          } else {
            tma2(&tmW2t, dst, b, 192 + 32 * r, 448 * ps + 224 * r);
            tma2(&tmW2t, dst + 14336, b, 192 + 32 * r, 448 * ps + 224 * (r ^ 1));
          }
        }
      }
    }
  } else {
    const int w = warp & 3, wt = tid & 127, tile = wg;
    const uint32_t epoch = g_epoch[blockIdx.x];
    uint2 dd;
    if (conv) {
      dd = __ldg(reinterpret_cast<const uint2*>(ssmD + quad * 4));
#pragma unroll
      for (int ch = 0; ch < 4; ch++)
        asm volatile("cp.async.cg.shared.global [%0], [%1], 16;" ::"r"(sb + OFF_SSM + ch * SSM_CH + (tid & 1) * SSM_PL + (127 - (tid >> 1)) * 16),
                     "l"(ssmk + (size_t)(quad * 4 + ch) * S_ + tid * 8) : "memory");
      if (tid < 128) sts32(sb + OFF_SSM + (tid >> 4) * SSM_PL + 2048 + (tid & 15) * 4, 0);
      else sts32(sb + OFF_TAB + ((tid - 128) >> 5) * TAB_PL + lane * 4, 0);
    }
    if (elect()) {
      const uint32_t b = bars + 32 * warp;
      const uint32_t ce = wg == 0 ? (r ? 1 : 4) : (warp < 6 ? 1 : 8), co = wg == 0 ? 5 - ce : ce;
      mbar_init(b, ce); mbar_init(b + 8, co); mbar_init(b + 16, ce); mbar_init(b + 24, co);
      if (wg == 0) { mbar_expect(b + 8 - 8 * r, 2048); mbar_expect(b + 24 - 8 * r, 2048); }
      if (warp == 5) mbar_expect(bars + 8 * B_Q, 14336);
      asm volatile("fence.mbarrier_init.release.cluster;" ::: "memory");
    }
    __syncwarp();
    asm volatile("barrier.cluster.arrive.relaxed.aligned;" ::: "memory");
    asm volatile("setmaxnreg.inc.sync.aligned.u32 %0;" ::"n"(REG_M));
    const uint32_t tag0 = (epoch * 2 + 2) << 16;
    if (tid == 0) TS(60);
    asm volatile("barrier.cluster.wait.aligned;" ::: "memory");
    if (tid == 0) TS(61);
    if (conv) {
      const int t = lane & 3, g = lane >> 2;
      const bool g2 = g >= 4, t3 = t == 0;
      const int rlow = (g & 3) + 4 * w, x0 = rlow + 32 * (g >> 2) - 2 * t;
      uint32_t fo[4];
#pragma unroll
      for (int k = 0; k < 4; k++) {
        const int y = x0 + (k == 1 ? 16 : k == 2 ? -8 : k == 3 ? 8 : 0);
        fo[k] = sb + OFF_TAB + 128 + 4 * (y ^ ((y >> 1) & 16));
      }
      float acc[4][36];
#pragma unroll
      for (int ch = 0; ch < 4; ch++)
#pragma unroll
        for (int i = 32; i < 36; i++) acc[ch][i] = 0.f;
      uint32_t fa[2][4][4];
      asm volatile("cp.async.wait_all;" ::: "memory");
      asm volatile("fence.proxy.async.shared::cta;" ::: "memory");
      asm volatile("bar.sync 1, 256;" ::: "memory");
      if (wt == 0) TS(0 + 16 * wg);
      const uint32_t dB = desc_lo(sb + OFF_SSM, SSM_PL);
      if (wg == 1) {
#pragma unroll
        for (int J = 0; J < 16; J++) {
          if (!(J & 1)) mbar_wait(bars + 8 * (B_TAB + (J >> 1)), 0);
#pragma unroll
          for (int ch = 0; ch < 4; ch++)
#pragma unroll
            for (int k = 0; k < 4; k++) fa[J & 1][ch][k] = lds32(fo[k] + ch * TAB_PL + 256 * J);
          WG_FENCE();
#pragma unroll
          for (int ch = 0; ch < 4; ch++) wg_rs<72, 0, HI_NONE>(acc[ch], fa[J & 1][ch], dB + ((ch * SSM_CH) >> 4) + 4 * J, J > 0);
          WG_COMMIT();
          WG_WAIT(1);
        }
#pragma unroll
        for (int k = 0; k < 4; k++) fo[k] += 4096;
      }
      const int src1 = (lane & ~3) | ((t + 1) & 3), src2 = ((lane & ~3) ^ 16) | ((g2 ? t - 1 : t + 1) & 3);
      const int tok0 = 1024 * wg + 16 * (g2 ? ((9 - 2 * t) & 7) : 6 - 2 * t) + rlow;
      const uint32_t ua = sb + OFF_TAB + 128 + 4 * (tok0 ^ ((tok0 >> 1) & 16));
      uint4* yp = g_Y + (size_t)((tok0 >> 1) * 112 + quad) * 2 + (tok0 & 1);
      ConvCarry cy;
      auto emit = [&](const float* o, int i) {
        const uint32_t u0 = lds32(ua + 512 * i), u1 = lds32(ua + 512 * i + TAB_PL);
        const uint32_t u2 = lds32(ua + 512 * i + 2 * TAB_PL), u3 = lds32(ua + 512 * i + 3 * TAB_PL);
        const uint32_t y01 = badd2(pack2(o[0], o[1]), bmul2(prmt(u0, u1, 0x5410), dd.x));
        const uint32_t y23 = badd2(pack2(o[2], o[3]), bmul2(prmt(u2, u3, 0x5410), dd.y));
        ll_st(yp + (size_t)i * (64 * 224), y01, y23, 0, tag0);
      };
#define CONV_STEP(j)                                                                                        \
  {                                                                                                         \
    if (!((j) & 1)) mbar_wait(bars + 8 * (B_TAB + ((j) >> 1)) + 64 * wg, 0);                                \
    _Pragma("unroll") for (int ch = 0; ch < 4; ch++)                                                        \
      _Pragma("unroll") for (int k = 0; k < 4; k++) fa[(j) & 1][ch][k] = lds32(fo[k] + ch * TAB_PL + 256 * (j)); \
    WG_FENCE();                                                                                             \
    _Pragma("unroll") for (int ch = 0; ch < 4; ch++)                                                        \
      wg_rs<64 - 8 * ((j) >> 1), 0, HI_NONE>(acc[ch], fa[(j) & 1][ch], dB + ((ch * SSM_CH) >> 4) + 64 + 4 * (j), (j) > 0 ? 1 : wg); \
    WG_COMMIT();                                                                                            \
    if ((j) & 1) {                                                                                          \
      float o[4];                                                                                           \
      conv_fold<((j) >> 1) - 1>(acc, cy, o, src1, src2, t3, g2);                                            \
      if ((j) >= 3) emit(o, ((j) >> 1) - 1);                                                                \
    }                                                                                                       \
    if ((j) < 15) WG_WAIT(1);                                                                               \
  }
      CONV_STEP(0) CONV_STEP(1) CONV_STEP(2) CONV_STEP(3) CONV_STEP(4) CONV_STEP(5) CONV_STEP(6) CONV_STEP(7)
      CONV_STEP(8) CONV_STEP(9) CONV_STEP(10) CONV_STEP(11) CONV_STEP(12) CONV_STEP(13) CONV_STEP(14) CONV_STEP(15)
#undef CONV_STEP
      WG_WAIT(0);
      if (wt == 0) TS(1 + 16 * wg);
      {
        float o[4];
        conv_fold<7>(acc, cy, o, src1, src2, t3, g2);
        emit(o, 7);
      }
      warp_arrive(bars + 8 * B_CFREE1, lane);
      if (wt == 0) TS(2 + 16 * wg);
    }
    if (wg == 1) turn_give(2);

#pragma unroll 1
    for (int layer = 0;; layer++) {
      const uint32_t tag = tag0 + (layer << 16);
      {
        const int t = lane & 3, rb = (lane >> 2) & 1, c2 = (lane >> 3) & 1, nh = lane >> 4;
        const uint32_t area = sb + OFF_H + tile * STG_TILE;
        const uint32_t colp = 2 * (nh * 256 + 32 * c2 + 2 * t), cols = 2 * (nh * 256 + 24 + 2 * t + c2);
        const uint32_t fixp = (nh & c2) * 448, fixs = nh * 448;
        const uint32_t stg = area + 7168 + (2 * w + rb) * STG_PITCH + nh * 32;
        const int blk = (gi * 2 + tile) * 8 + 2 * ps + r, pos = (nh * 8 + c2) * 32 + (2 * w + rb) * 4 + t;
        uint4* st = g_St + (blockIdx.x * 2 + tile) * 1024 + wt;
        float v[28], base, mean, rstd;
        uint32_t yw[4][4];
        float s1[4] = {0.f, 0.f, 0.f, 0.f}, s2[4] = {0.f, 0.f, 0.f, 0.f};
        if (layer == 0) {
          const uint4* yp = g_Y + (size_t)(tile * 512 + own * 4 + w) * 224 + lane;
          mbar_wait(bars + 8 * B_Q, 0);
          const uint32_t qa = area + (2 * w + rb) * 896;
#pragma unroll
          for (int p = 0; p < 4; p++) {
#pragma unroll
            for (int j = 0; j < 3; j++) {
              const uint32_t x = lds32(qa + colp + 112 * p + 16 * j - (p == 3 ? fixp : 0));
              v[7 * p + 2 * j] = blo(x); v[7 * p + 2 * j + 1] = bhi(x);
            }
            v[7 * p + 6] = blo(lds16(qa + cols + 112 * p - (p == 3 ? fixs : 0)));
          }
          base = row_sum(tree_sum<28>(v)) * (1.f / 448.f);
#pragma unroll
          for (int i = 0; i < 28; i++) v[i] -= base;
          acc_moments<28>(v, s1, s2);
          finish_moments(s1, s2, mean, rstd);
          uint32_t raw[7][4];
          while (true) {
#pragma unroll
            for (int k = 0; k < 7; k++) ll_ld(raw[k], yp + 32 * k);
            if (!ll_bad<7>(raw, tag0) || --budget <= 0) break;
            if (!conv) __nanosleep(200);
          }
          if (wt == 0) TS(33 + tile);
#pragma unroll
          for (int k = 0; k < 7; k++) {
            const int qd = 16 * k + (lane >> 1);
            sts64(area + 7168 + (2 * w + (lane & 1)) * STG_PITCH + qd * 8 + (qd >= 56 ? 32 : 0), raw[k][0], raw[k][1]);
          }
          __syncwarp();
#pragma unroll
          for (int p = 0; p < 4; p++) {
#pragma unroll
            for (int j = 0; j < 3; j++) yw[p][j] = lds32(stg + colp + 112 * p + 16 * j - (p == 3 ? fixp : 0));
            yw[p][3] = lds16(stg + cols + 112 * p - (p == 3 ? fixs : 0));
          }
        } else {
          const uint32_t tagp = tag - (1 << 16);
          const uint4* pr = g_P + (size_t)blk * 2048 + pos;
          uint32_t raw[16][4], xw[4][4];
#pragma unroll
          for (int p = 0; p < 4; p++) { const uint4 x4 = st[128 * p]; xw[p][0] = x4.x; xw[p][1] = x4.y; xw[p][2] = x4.z; xw[p][3] = x4.w; }
#pragma unroll
          for (int k = 0; k < 12; k++) ll_ld(raw[k], pr + (k & 3) * 512 + (k >> 2) * 64);
          if (layer == 1) {
#pragma unroll
            for (int p = 0; p < 4; p++) { const uint4 y4 = st[512 + 128 * p]; yw[p][0] = y4.x; yw[p][1] = y4.y; yw[p][2] = y4.z; yw[p][3] = y4.w; }
          }
#pragma unroll
          for (int k = 12; k < 16; k++) ll_ld(raw[k], pr + (k & 3) * 512 + (k >> 2) * 64);
          auto take = [&](int p) {
#pragma unroll
            for (int j = 0; j < 4; j++) {
              const float lo = (blo(raw[4 * p][j]) + blo(raw[4 * p + 1][j])) + (blo(raw[4 * p + 2][j]) + blo(raw[4 * p + 3][j]));
              float hi = 0.f;
              if (j < 3) hi = (bhi(raw[4 * p][j]) + bhi(raw[4 * p + 1][j])) + (bhi(raw[4 * p + 2][j]) + bhi(raw[4 * p + 3][j]));
              xw[p][j] = badd2(xw[p][j], pack2(lo, hi));
              v[7 * p + 2 * j] = blo(xw[p][j]);
              if (j < 3) v[7 * p + 2 * j + 1] = bhi(xw[p][j]);
            }
          };
          while (ll_bad<4>(raw + 8, tagp) && --budget > 0) {
#pragma unroll
            for (int k = 8; k < 12; k++) ll_ld(raw[k], pr + (k & 3) * 512 + (k >> 2) * 64);
          }
          while (ll_bad<8>(raw, tagp) && --budget > 0) {
#pragma unroll
            for (int k = 0; k < 8; k++) ll_ld(raw[k], pr + (k & 3) * 512 + (k >> 2) * 64);
          }
          if (wt == 0) TS(64 + 2 * layer + tile);
          take(0); take(1); take(2);
          if (layer == 1) {
            base = row_sum(tree_sum<21>(v)) * (1.f / 336.f);
#pragma unroll
            for (int i = 0; i < 21; i++) v[i] -= base;
            acc_moments<21>(v, s1, s2);
          } else {
            if (tile == 0) mbar_wait(bars + 8 * B_HCONS, 0);
#pragma unroll
            for (int p = 0; p < 3; p++) {
#pragma unroll
              for (int j = 0; j < 3; j++) sts32(stg + colp + 112 * p + 16 * j, xw[p][j]);
              sts16(stg + cols + 112 * p, xw[p][3]);
            }
          }
          while (ll_bad<4>(raw + 12, tagp) && --budget > 0) {
#pragma unroll
            for (int k = 12; k < 16; k++) ll_ld(raw[k], pr + (k & 3) * 512 + (k >> 2) * 64);
          }
          if (wt == 0) TS(33 + 2 * layer + tile);
          take(3);
          if (layer == 2) {
#pragma unroll
            for (int j = 0; j < 3; j++) sts32(stg + colp + 336 + 16 * j - fixp, xw[3][j]);
            sts16(stg + cols + 336 - fixs, xw[3][3]);
            __syncwarp();
            uint4* op = reinterpret_cast<uint4*>(out + (size_t)(tile * 1024 + own * 8 + 2 * w) * D_);
#pragma unroll
            for (int k = 0; k < 4; k++) {
              const int ci = 32 * k + lane;
              if (ci < 112) {
                const int row = ci >= 56, c = ci - 56 * row;
                uint32_t x[4];
                lds128(x, area + 7168 + (2 * w + row) * STG_PITCH + c * 16 + (c >= 28 ? 32 : 0));
                op[ci] = make_uint4(x[0], x[1], x[2], x[3]);
              }
            }
            if (wt == 0) TS(44 + tile);
            break;
          }
#pragma unroll
          for (int i = 21; i < 28; i++) v[i] -= base;
          acc_moments<7>(v + 21, s1, s2);
          finish_moments(s1, s2, mean, rstd);
        }
        base += mean;
#pragma unroll
        for (int k = 0; k < 4; k++) s1[k] = s2[k] = 0.f;
#pragma unroll
        for (int p = 0; p < 4; p++) {
#pragma unroll
          for (int j = 0; j < 4; j++) {
            v[7 * p + 2 * j] = (v[7 * p + 2 * j] - mean) * fmaf(rstd, blo(yw[p][j]), 1.f);
            if (j < 3) v[7 * p + 2 * j + 1] = (v[7 * p + 2 * j + 1] - mean) * fmaf(rstd, bhi(yw[p][j]), 1.f);
          }
        }
        acc_moments<28>(v, s1, s2);
        finish_moments(s1, s2, mean, rstd);
        const float nb = -mean * rstd;
        uint4* xo = g_X + (size_t)blk * 512 + pos;
#pragma unroll
        for (int p = 0; p < 4; p++) {
          uint32_t x[4];
#pragma unroll
          for (int j = 0; j < 3; j++) x[j] = pack2(fmaf(v[7 * p + 2 * j], rstd, nb), fmaf(v[7 * p + 2 * j + 1], rstd, nb));
          x[3] = pack2(fmaf(v[7 * p + 6], rstd, nb), 0.f) | tag;
          ll_st(xo + p * 64, x[0], x[1], x[2], x[3]);
        }
        if (wt == 0) TS(40 + 2 * layer + tile);
#pragma unroll
        for (int p = 0; p < 4; p++) {
          st[128 * p] = make_uint4(pack2(v[7 * p] + base, v[7 * p + 1] + base), pack2(v[7 * p + 2] + base, v[7 * p + 3] + base),
                                   pack2(v[7 * p + 4] + base, v[7 * p + 5] + base), pack2(v[7 * p + 6] + base, 0.f));
          if (layer == 0) st[512 + 128 * p] = make_uint4(yw[p][0], yw[p][1], yw[p][2], yw[p][3]);
        }
        if (layer == 0 && tile == 1 && lane == 0) mbar_arrive_remote(mapa(bars + 8 * B_HFREE, r ^ 1));
      }
      const uint4* xp = g_X + (size_t)((gi * 2 + tile) * 8 + 2 * w) * 512 + lane;
      uint4* pp = g_P + (size_t)(((gi * 2 + tile) * 8 + 2 * w) * 4 + ps) * 512 + r * 256 + lane;
      uint32_t h[28][4];
      {
        float acc[112];
        uint32_t raw[XB][4][4], af[2][4][4], carry[2];
        auto xload = [&](int hg) {
#pragma unroll
          for (int k = 0; k < 4; k++) ll_ld(raw[hg % XB][k], xp + (k >> 1) * 512 + (hg * 2 + (k & 1)) * 32);
        };
        auto xtake = [&](int hg) {
          uint32_t(*rw)[4] = raw[hg % XB];
          while (ll_bad<4>(rw, tag) && --budget > 0) xload(hg);
#pragma unroll
          for (int hh = 0; hh < 2; hh++) {
            const uint32_t* c0 = rw[2 * hh];
            const uint32_t* c1 = rw[2 * hh + 1];
            const uint32_t p3 = prmt(c0[3], c1[3], 0x5410);
            if (!(hg & 1)) {
              af[0][0][hh] = c0[0] ^ zero; af[0][0][2 + hh] = c0[1] ^ zero;
              af[0][1][hh] = c0[2] ^ zero; af[0][1][2 + hh] = p3;
              af[0][2][hh] = c1[0] ^ zero; af[0][2][2 + hh] = c1[1] ^ zero;
              carry[hh] = c1[2] ^ zero;
            } else {
              af[1][0][hh] = carry[hh] | zero; af[1][0][2 + hh] = c0[0] ^ zero;
              af[1][1][hh] = c0[1] ^ zero; af[1][1][2 + hh] = c0[2] ^ zero;
              af[1][2][hh] = p3; af[1][2][2 + hh] = c1[0] ^ zero;
              af[1][3][hh] = c1[1] ^ zero; af[1][3][2 + hh] = c1[2] ^ zero;
            }
          }
          if (hg + XB < 8) xload(hg + XB);
        };
        do {
          xload(0);
          xload(1);
          if (XB > 2) xload(2);
        } while (ll_bad<4 * XB>(raw[0], tag) && --budget > 0);
        xtake(0);
        if (wt == 0) TS(3 + 16 * wg + 6 * layer);
        mbar_wait(bars + 8 * B_WFULL, 0);
        turn_wait(2 + wg);
        if (wt == 0) TS(4 + 16 * wg + 6 * layer);
        const uint32_t dm = desc_lo(sb, 4096), dt = dm + (12288 >> 4);
#pragma unroll
        for (int hg = 0; hg < 8; hg++) {
          const int s0 = 7 * (hg >> 1) + 3 * (hg & 1), ns = 3 + (hg & 1);
          WG_FENCE();
#pragma unroll
          for (int k = 0; k < ns; k++) {
            const int s = s0 + k;
            wg_rs<192, 1, HI_128>(acc, af[hg & 1][k], dm + (((s >> 1) * 14336 + (s & 1) * 2048) >> 4), s > 0);
            wg_rs<32, 1, HI_64>(acc + 96, af[hg & 1][k], dt + (((s >> 1) * 14336 + (s & 1) * 1024) >> 4), s > 0);
          }
          WG_COMMIT();
          if (hg < 7) {
            if (hg != 5) STALL(sw_, mbar_wait(bars + 8 * (B_WFULL + (hg < 5 ? hg + 1 : 6)), 0));
            STALL(sg_, WG_WAIT(1));
            if (hg >= 2) warp_arrive(bars + 8 * (B_WEMPTY + hg - 2), lane);
            STALL(sx_, xtake(hg + 1));
          }
        }
        turn_give(3 - wg);
        WG_WAIT(1);
        warp_arrive(bars + 8 * (B_WEMPTY + 5), lane);
        WG_WAIT(0);
        warp_arrive(bars + 8 * (B_WEMPTY + 6), lane);
        pin<112>(acc);
        if (wt == 0) TS(5 + 16 * wg + 6 * layer);
        const uint32_t hrem = mapa(sb + OFF_H + wt * 16, r ^ 1), brem = mapa(bars + 8 * (B_HFULL + tile), r ^ 1);
        mbar_wait(bars + 8 * (B_HFREE + tile), layer);
#pragma unroll
        for (int s = 0; s < 14; s++) {
          float e[8];
#pragma unroll
          for (int k = 0; k < 8; k++) {
            const float x = 0.5f * acc[8 * s + k];
            float th;
            asm("tanh.approx.f32 %0, %1;" : "=f"(th) : "f"(x));
            e[k] = fmaf(x, th, x);
          }
#pragma unroll
          for (int k = 0; k < 4; k++) h[s][k] = pack2(e[2 * k], e[2 * k + 1]);
          asm volatile("st.async.shared::cluster.mbarrier::complete_tx::bytes.v4.u32 [%0], {%1,%2,%3,%4}, [%5];" ::"r"(hrem + s * 2048),
                       "r"(h[s][0]), "r"(h[s][1]), "r"(h[s][2]), "r"(h[s][3]), "r"(brem) : "memory");
        }
      }
      if (wt == 0) TS(88 + 2 * layer + tile);
      mbar_wait(bars + 8 * (B_HFULL + tile), layer);
      if (wt == 0 && layer == 0) mbar_expect(bars + 8 * (B_HFULL + tile), SLOT);
#pragma unroll
      for (int s = 0; s < 14; s++) lds128(h[14 + s], sb + OFF_H + s * 2048 + wt * 16);
      __syncwarp();
      if (lane == 0) {
        if (tile & layer) mbar_arrive(bars + 8 * B_HCONS);
        else mbar_arrive_remote(mapa(bars + 8 * (B_HFREE + (tile ^ 1)), r ^ 1));
      }
      if (wt == 0) TS(6 + 16 * wg + 6 * layer);
      {
        float acc[2][32];
        uint32_t pk[2][28];
        const uint32_t d0 = desc_lo(sb, 0);
        const uint32_t om = d0 + 256 * r, ot = d0 + 1536 - 1536 * r, pm = d0 + 256 - 256 * r, pt = d0 + 1536 * r;
        const uint32_t om2 = d0 + 128 * r, ot2 = d0 + 768 - 768 * r, pm2 = d0 + 128 - 128 * r, pt2 = d0 + 768 * r;
        auto mma = [&](int p, int s) {
          const int half = s >= 14, k = s - 14 * half, kk = k < 12 ? k : k - 12;
          if (p < 3) wg_rs<64, 1, HI_128>(acc[p & 1], h[s], (k < 12 ? (half ? pm : om) : (half ? pt : ot)) + (((2 * p + half) * SLOT + kk * 2048) >> 4), s > 0);
          else wg_rs<32, 1, HI_64>(acc[1], h[s], (k < 12 ? (half ? pm2 : om2) : (half ? pt2 : ot2)) + ((6 * SLOT + half * 14336 + kk * 1024) >> 4), s > 0);
        };
        auto epi = [&](int p) {
          float* a = acc[p & 1];
          if (p < 3) pin<32>(a); else pin<16>(a);
#pragma unroll
          for (int i = 0; i < (p < 3 ? 8 : 4); i++) {
            pk[0][8 * p + i] = pack2(a[4 * i], a[4 * i + 1]);
            pk[1][8 * p + i] = pack2(a[4 * i + 2], a[4 * i + 3]);
          }
#pragma unroll
          for (int hh = 0; hh < 2; hh++) {
            const uint32_t* k7 = pk[hh] + 7 * p;
            ll_st(pp + hh * 2048 + (2 * p) * 32, k7[0], k7[1], k7[2], prmt(k7[3], tag, 0x7610));
            ll_st(pp + hh * 2048 + (2 * p + 1) * 32, k7[4], k7[5], k7[6], prmt(k7[3], tag, 0x7632));
          }
        };
        turn_wait(2 + wg);
        if (wt == 0) TS(7 + 16 * wg + 6 * layer);
#pragma unroll
        for (int p = 0; p < 4; p++) {
          STALL(sw_, mbar_wait(bars + 8 * (B_WFULL + 2 * p), 1));
          WG_FENCE();
#pragma unroll
          for (int s = 0; s < 6; s++) mma(p, s);
          WG_COMMIT();
          if (p > 0) {
            WG_WAIT(1);
            warp_arrive(bars + 8 * (B_WEMPTY + 2 * p - 1), lane);
            epi(p - 1);
          }
#pragma unroll
          for (int s = 6; s < 14; s++) mma(p, s);
          WG_COMMIT();
          if (p < 3) STALL(sw_, mbar_wait(bars + 8 * (B_WFULL + 2 * p + 1), 1));
#pragma unroll
          for (int s = 14; s < 20; s++) mma(p, s);
          WG_COMMIT();
          if (p < 3) {
            WG_WAIT(1);
            warp_arrive(bars + 8 * (B_WEMPTY + 2 * p), lane);
          }
#pragma unroll
          for (int s = 20; s < 28; s++) mma(p, s);
          WG_COMMIT();
        }
        if (!(tile & layer)) turn_give(3 - wg);
        WG_WAIT(0);
        warp_arrive(bars + 8 * (B_WEMPTY + 6), lane);
        epi(3);
        if (wt == 0) TS(8 + 16 * wg + 6 * layer);
      }
    }
    if (tid == 128) { g_epoch[blockIdx.x] = epoch + 1; GT(63); }
  }
}

typedef CUresult (*EncodeFn)(CUtensorMap*, CUtensorMapDataType, cuuint32_t, void*, const cuuint64_t*, const cuuint64_t*,
                             const cuuint32_t*, const cuuint32_t*, CUtensorMapInterleave, CUtensorMapSwizzle,
                             CUtensorMapL2promotion, CUtensorMapFloatOOBfill);

void encode(EncodeFn fn, CUtensorMap* m, const void* base, int rank, const cuuint64_t* dims, const cuuint64_t* strides,
            const cuuint32_t* box, CUtensorMapSwizzle sw, CUtensorMapL2promotion pr) {
  const cuuint32_t es[3] = {1, 1, 1};
  fn(m, CU_TENSOR_MAP_DATA_TYPE_BFLOAT16, rank, const_cast<void*>(base), dims, strides, box, es,
     CU_TENSOR_MAP_INTERLEAVE_NONE, sw, pr, CU_TENSOR_MAP_FLOAT_OOB_FILL_NONE);
}

}

extern "C" void kernel_launch(void* const* d_in, const int* in_sizes, int n_in, void* d_out, int out_size) {
  const __nv_bfloat16* q = (const __nv_bfloat16*)d_in[0];
  const __nv_bfloat16* k = (const __nv_bfloat16*)d_in[1];
  const __nv_bfloat16* v = (const __nv_bfloat16*)d_in[2];
  const __nv_bfloat16* shiftk = (const __nv_bfloat16*)d_in[3];
  const __nv_bfloat16* ssmk = (const __nv_bfloat16*)d_in[4];
  const __nv_bfloat16* ssmD = (const __nv_bfloat16*)d_in[5];
  const __nv_bfloat16* w1 = (const __nv_bfloat16*)d_in[7];
  const __nv_bfloat16* w2 = (const __nv_bfloat16*)d_in[8];

  EncodeFn fn = nullptr;
  cudaDriverEntryPointQueryResult qr;
  cudaGetDriverEntryPoint("cuTensorMapEncodeTiled", (void**)&fn, cudaEnableDefault, &qr);
  cudaFuncSetAttribute(h3ffn_kernel, cudaFuncAttributeMaxDynamicSharedMemorySize, SMEM_TOTAL);

  CUtensorMap tmK, tmV, tmW1m, tmW1t, tmW2m, tmW2t;
  {
    const cuuint64_t dims[2] = {D_, S_}, str[1] = {D_ * 2};
    const cuuint32_t box[2] = {8, 132};
    encode(fn, &tmK, k, 2, dims, str, box, CU_TENSOR_MAP_SWIZZLE_NONE, CU_TENSOR_MAP_L2_PROMOTION_L2_128B);
    encode(fn, &tmV, v, 2, dims, str, box, CU_TENSOR_MAP_SWIZZLE_NONE, CU_TENSOR_MAP_L2_PROMOTION_L2_128B);
  }
  {
    const cuuint64_t dims[3] = {64, D_, F_ / 64}, str[2] = {F_ * 2, 128};
    const cuuint32_t box[3] = {64, 32, 3};
    encode(fn, &tmW1m, w1, 3, dims, str, box, CU_TENSOR_MAP_SWIZZLE_128B, CU_TENSOR_MAP_L2_PROMOTION_NONE);
  }
  {
    const cuuint64_t dims[2] = {F_, D_}, str[1] = {F_ * 2};
    const cuuint32_t box[2] = {32, 32};
    encode(fn, &tmW1t, w1, 2, dims, str, box, CU_TENSOR_MAP_SWIZZLE_64B, CU_TENSOR_MAP_L2_PROMOTION_NONE);
  }
  {
    const cuuint64_t dims[2] = {D_, F_}, str[1] = {D_ * 2};
    const cuuint32_t boxm[2] = {64, 224}, boxt[2] = {32, 224};
    encode(fn, &tmW2m, w2, 2, dims, str, boxm, CU_TENSOR_MAP_SWIZZLE_128B, CU_TENSOR_MAP_L2_PROMOTION_NONE);
    encode(fn, &tmW2t, w2, 2, dims, str, boxt, CU_TENSOR_MAP_SWIZZLE_64B, CU_TENSOR_MAP_L2_PROMOTION_NONE);
  }
  h3ffn_kernel<<<128, NTHREADS, SMEM_TOTAL>>>(tmK, tmV, tmW1m, tmW1t, tmW2m, tmW2t, q, shiftk, ssmk, ssmD, w1, w2,
                                              (__nv_bfloat16*)d_out, 0u);
}
```

```cpp
#include <cuda_runtime.h>
#include <cuda_bf16.h>
#include <cuda.h>
#include <stdint.h>

constexpr int S_ = 2048, D_ = 448, F_ = 1792;
constexpr int NTHREADS = 384;
constexpr int REG_M = 232, REG_H = 40;
constexpr int KV_AHEAD = 3;
constexpr uint32_t SLOT = 28672;
constexpr uint32_t OFF_H = 7 * SLOT, OFF_BAR = 8 * SLOT + 1024, OFF_RED = OFF_BAR + 640, SMEM_TOTAL = OFF_RED + 1024;
constexpr uint32_t OFF_KV = 4 * SLOT, KV_HALF = 2176, KV_BLK = 2 * KV_HALF, KV_BYTES = 2 * 132 * 16;
constexpr uint32_t OFF_SSM = OFF_KV + 8 * KV_BLK, SSM_PL = 2112, SSM_CH = 2 * SSM_PL;
constexpr uint32_t OFF_TAB = OFF_SSM + 4 * SSM_CH, TAB_PL = 8224;
static_assert(OFF_TAB + 4 * TAB_PL <= OFF_H, "conv scratch overflow");
constexpr uint32_t STG_PITCH = 912, STG_HALF = 8 * STG_PITCH, STG_TILE = 2 * STG_HALF;
enum { B_TAB = 0, B_WFULL = 16, B_Q = 23, B_WEMPTY = 24, B_CFREE1 = 31, B_KV = 32, B_HFREE = 40,
       B_CFREE0 = 42, B_HCONS = 43, B_SPILL = 46, B_HFULL = 48  , B_QST = 64, B_YRDY = 66, B_G1S = 68 };

constexpr uint32_t TAGM = 0x40004000u;
constexpr uint32_t X_UP = 0x02800280u, P_UP = 0x20002000u, P_DOWN2 = 0x1F801F80u;

__device__ uint4 dg_Y[2 * 128 * 448];
__device__ uint4 dg_X[16 * 2 * 8 * 448];
__device__ uint4 dg_P[16 * 2 * 8 * 4 * 448];
__device__ unsigned dg_epoch[128];

__device__ __forceinline__ void mbar_init(uint32_t b, uint32_t c) { asm volatile("mbarrier.init.shared::cta.b64 [%0], %1;" ::"r"(b), "r"(c) : "memory"); }
__device__ __forceinline__ void mbar_expect(uint32_t b, uint32_t bytes) { asm volatile("mbarrier.arrive.expect_tx.shared::cta.b64 _, [%0], %1;" ::"r"(b), "r"(bytes) : "memory"); }
__device__ __forceinline__ void mbar_arrive(uint32_t b) { asm volatile("mbarrier.arrive.shared::cta.b64 _, [%0];" ::"r"(b) : "memory"); }
__device__ __forceinline__ void mbar_arrive_remote(uint32_t b) { asm volatile("mbarrier.arrive.shared::cluster.b64 _, [%0];" ::"r"(b) : "memory"); }
__device__ __forceinline__ void mbar_wait_b(uint32_t b, uint32_t parity, int& budget) {
  asm volatile("{.reg .pred p;\nMW: add.s32 %0, %0, -1; mbarrier.try_wait.parity.shared::cta.b64 p, [%1], %2;\n"
               "setp.gt.and.s32 p, %0, 0, !p; @p bra.uni MW;}" : "+r"(budget) : "r"(b), "r"(parity) : "memory");
}
__device__ __forceinline__ void mbar_wait2_b(uint32_t b, uint32_t parity, int& budget) {
  asm volatile("{.reg .pred p, q;\nMW: add.s32 %0, %0, -1; mbarrier.try_wait.parity.shared::cta.b64 p, [%1], %2;\n"
               "mbarrier.try_wait.parity.shared::cta.b64 q, [%1+8], %2; and.pred p, p, q;\n"
               "setp.gt.and.s32 p, %0, 0, !p; @p bra.uni MW;}" : "+r"(budget) : "r"(b), "r"(parity) : "memory");
}
#define mbar_wait(b, parity) mbar_wait_b(b, parity, budget)
__device__ __forceinline__ void warp_arrive(uint32_t b, int lane) { __syncwarp(); if (lane == 0) mbar_arrive(b); }
__device__ __forceinline__ uint32_t mapa(uint32_t a, uint32_t r) { uint32_t o; asm("mapa.shared::cluster.u32 %0, %1, %2;" : "=r"(o) : "r"(a), "r"(r)); return o; }
__device__ __forceinline__ void tma2(const CUtensorMap* m, uint32_t dst, uint32_t bar, int x, int y) {
  asm volatile("cp.async.bulk.tensor.2d.shared::cluster.global.mbarrier::complete_tx::bytes [%0], [%1, {%3, %4}], [%2];" ::"r"(dst), "l"(m), "r"(bar), "r"(x), "r"(y) : "memory");
}
__device__ __forceinline__ void tma3(const CUtensorMap* m, uint32_t dst, uint32_t bar, int x, int y, int z) {
  asm volatile("cp.async.bulk.tensor.3d.shared::cluster.global.mbarrier::complete_tx::bytes [%0], [%1, {%3, %4, %5}], [%2];" ::"r"(dst), "l"(m), "r"(bar), "r"(x), "r"(y), "r"(z) : "memory");
}
__device__ __forceinline__ void bulk_g2s(uint32_t dst, const void* src, uint32_t bytes, uint32_t bar) {
  asm volatile("cp.async.bulk.shared::cluster.global.mbarrier::complete_tx::bytes [%0], [%1], %2, [%3];" ::"r"(dst), "l"(src), "r"(bytes), "r"(bar) : "memory");
}
__device__ __forceinline__ void ll_ld(uint32_t* v, const uint4* p) {
  asm volatile("{.reg .b128 x; ld.relaxed.gpu.global.b128 x, [%4]; mov.b128 {%0,%1,%2,%3}, x;}" : "=r"(v[0]), "=r"(v[1]), "=r"(v[2]), "=r"(v[3]) : "l"(p) : "memory");
}
__device__ __forceinline__ void ll_ld_if(uint32_t* v, const uint4* p, bool on) {
  asm volatile("{.reg .pred q; setp.ne.b32 q, %5, 0; mov.b32 %0, 0; mov.b32 %1, 0; mov.b32 %2, 0; mov.b32 %3, 0;"
               " @q ld.relaxed.gpu.global.v4.u32 {%0,%1,%2,%3}, [%4];}"
               : "=r"(v[0]), "=r"(v[1]), "=r"(v[2]), "=r"(v[3]) : "l"(p), "r"((int)on) : "memory");
}
__device__ __forceinline__ void ll_retry(uint32_t* v, const uint4* p, uint32_t tag) {
  asm volatile("{.reg .pred q; .reg .b32 t; xor.b32 t, %0, %5; and.b32 t, t, 0x40004000; setp.ne.b32 q, t, 0;"
               " @q ld.relaxed.gpu.global.v4.u32 {%0,%1,%2,%3}, [%4];}"
               : "+r"(v[0]), "+r"(v[1]), "+r"(v[2]), "+r"(v[3]) : "l"(p), "r"(tag) : "memory");
}
__device__ __forceinline__ bool ll_bad4(uint32_t (*v)[4], uint32_t tag) {
  return __any_sync(0xffffffffu, ((v[0][0] ^ tag) | (v[1][0] ^ tag) | (v[2][0] ^ tag) | (v[3][0] ^ tag)) & TAGM);
}
template <int STRIDE, bool LANEWISE>
__device__ __forceinline__ void ll_wait4(uint32_t (*v)[4], const uint4* p, uint32_t tag, bool never, int& budget) {
  uint32_t g = tag;
  asm volatile("{.reg .pred q; setp.ne.b32 q, %1, 0; @q ld.volatile.shared.u32 %0, [%0];}" : "+r"(g) : "r"((int)never) : "memory");
  if (__builtin_expect(ll_bad4(v, g), 0)) {
#pragma unroll 1
    do {
#pragma unroll
      for (int k = 0; k < 4; k++) {
        if (LANEWISE) ll_retry(v[k], p + k * STRIDE, tag);
        else ll_ld(v[k], p + k * STRIDE);
      }
    } while (ll_bad4(v, tag) && --budget > 0);
  }
}
__device__ __forceinline__ void ll_st(uint4* p, uint32_t a, uint32_t b, uint32_t c, uint32_t d) {
  asm volatile("{.reg .b128 x; mov.b128 x, {%1,%2,%3,%4}; st.relaxed.gpu.global.b128 [%0], x;}" ::"l"(p), "r"(a), "r"(b), "r"(c), "r"(d) : "memory");
}
__device__ __forceinline__ uint32_t lds32(uint32_t a) { uint32_t v; asm volatile("ld.shared.u32 %0, [%1];" : "=r"(v) : "r"(a) : "memory"); return v; }
__device__ __forceinline__ uint32_t lds32_if(uint32_t a, bool on) {
  uint32_t v;
  asm volatile("{.reg .pred q; setp.ne.b32 q, %2, 0; mov.b32 %0, 0; @q ld.shared.u32 %0, [%1];}" : "=r"(v) : "r"(a), "r"((int)on) : "memory");
  return v;
}
__device__ __forceinline__ void lds128(uint32_t* v, uint32_t a) { asm volatile("ld.shared.v4.u32 {%0,%1,%2,%3}, [%4];" : "=r"(v[0]), "=r"(v[1]), "=r"(v[2]), "=r"(v[3]) : "r"(a) : "memory"); }
__device__ __forceinline__ void lds64(uint32_t* v, uint32_t a) { asm volatile("ld.shared.v2.u32 {%0,%1}, [%2];" : "=r"(v[0]), "=r"(v[1]) : "r"(a) : "memory"); }
__device__ __forceinline__ void sts32(uint32_t a, uint32_t v) { asm volatile("st.shared.u32 [%0], %1;" ::"r"(a), "r"(v) : "memory"); }
__device__ __forceinline__ void sts128(uint32_t a, uint32_t v0, uint32_t v1, uint32_t v2, uint32_t v3) { asm volatile("st.shared.v4.u32 [%0], {%1,%2,%3,%4};" ::"r"(a), "r"(v0), "r"(v1), "r"(v2), "r"(v3) : "memory"); }
__device__ __forceinline__ void st_async128(uint32_t a, uint32_t v0, uint32_t v1, uint32_t v2, uint32_t v3, uint32_t bar) {
  asm volatile("st.async.shared::cluster.mbarrier::complete_tx::bytes.v4.u32 [%0], {%1,%2,%3,%4}, [%5];" ::"r"(a), "r"(v0), "r"(v1), "r"(v2), "r"(v3), "r"(bar) : "memory");
}
__device__ __forceinline__ uint32_t mktag(uint32_t seq) { const uint32_t v = seq % 3 + 1; return ((v & 1) << 14) | ((v & 2) << 29); }
__device__ __forceinline__ uint32_t tagged(uint32_t w, uint32_t tag) { return (w & ~TAGM) | tag; }
__device__ __forceinline__ void sts64(uint32_t a, uint32_t v0, uint32_t v1) { asm volatile("st.shared.v2.u32 [%0], {%1,%2};" ::"r"(a), "r"(v0), "r"(v1) : "memory"); }
__device__ __forceinline__ uint32_t prmt(uint32_t a, uint32_t b, uint32_t s) { uint32_t o; asm("prmt.b32 %0, %1, %2, %3;" : "=r"(o) : "r"(a), "r"(b), "r"(s)); return o; }
__device__ __forceinline__ uint32_t pack2(float lo, float hi) { uint32_t o; asm("cvt.rn.bf16x2.f32 %0, %1, %2;" : "=r"(o) : "f"(hi), "f"(lo)); return o; }
__device__ __forceinline__ uint32_t bmul2(uint32_t a, uint32_t b) { uint32_t o; asm("mul.rn.bf16x2 %0, %1, %2;" : "=r"(o) : "r"(a), "r"(b)); return o; }
__device__ __forceinline__ uint32_t badd2(uint32_t a, uint32_t b) { uint32_t o; asm("add.rn.bf16x2 %0, %1, %2;" : "=r"(o) : "r"(a), "r"(b)); return o; }
__device__ __forceinline__ uint32_t bfma2(uint32_t a, uint32_t b, uint32_t c) { uint32_t o; asm("fma.rn.bf16x2 %0, %1, %2, %3;" : "=r"(o) : "r"(a), "r"(b), "r"(c)); return o; }
__device__ __forceinline__ float blo(uint32_t w) { return __uint_as_float(w << 16); }
__device__ __forceinline__ float bhi(uint32_t w) { return __uint_as_float(w & 0xFFFF0000u); }
constexpr uint32_t HI_NONE = 128 >> 4, HI_128 = (1024 >> 4) | (1u << 30), HI_64 = (512 >> 4) | (2u << 30);
__device__ __forceinline__ uint64_t mkdesc(uint32_t addr, uint32_t lbo, uint32_t hi, uint32_t zero) {
  return (uint64_t)(((addr & 0x3FFFF) >> 4) | ((lbo >> 4) << 16)) | ((uint64_t)(hi | zero) << 32);
}
__device__ __forceinline__ bool elect() {
  uint32_t p;
  asm volatile("{.reg .pred P; elect.sync _|P, 0xffffffff; selp.u32 %0, 1, 0, P;}" : "=r"(p));
  return p;
}
#define WG_FENCE() asm volatile("wgmma.fence.sync.aligned;" ::: "memory")
#define WG_COMMIT() asm volatile("wgmma.commit_group.sync.aligned;" ::: "memory")
#define WG_WAIT(n) asm volatile("wgmma.wait_group.sync.aligned %0;" ::"n"(n) : "memory")
template <int N> __device__ __forceinline__ void pin(float* d) {
#pragma unroll
  for (int i = 0; i < N; i++) asm volatile("" : "+f"(d[i])::"memory");
}
template <int N> __device__ __forceinline__ void pinu(uint32_t* d) {
#pragma unroll
  for (int i = 0; i < N; i++) asm volatile("" : "+r"(d[i])::"memory");
}
__device__ __forceinline__ void sched_fence(uint32_t zero) { asm volatile("{.reg .pred p; setp.ne.u32 p, %0, 0; @p nanosleep.u32 0;}" ::"r"(zero) : "memory"); }
__device__ __forceinline__ void turn_wait(int id) { asm volatile("bar.sync %0, 256;" ::"r"(id) : "memory"); }
__device__ __forceinline__ void turn_give(int id) { asm volatile("bar.arrive %0, 256;" ::"r"(id) : "memory"); }

template <int TB> __device__ __forceinline__ void wg_rs0_32(float* d, const uint32_t* a, uint64_t db) {
  asm volatile("{wgmma.mma_async.sync.aligned.m64n32k16.f32.bf16.bf16 "
    "{%0,%1,%2,%3,%4,%5,%6,%7,%8,%9,%10,%11,%12,%13,%14,%15}, "
    "{%16,%17,%18,%19}, %20, 0, 1, 1, %21;}"
    : "=f"(d[0]), "=f"(d[1]), "=f"(d[2]), "=f"(d[3]), "=f"(d[4]), "=f"(d[5]), "=f"(d[6]), "=f"(d[7]), "=f"(d[8]), "=f"(d[9]), "=f"(d[10]), "=f"(d[11]),
      "=f"(d[12]), "=f"(d[13]), "=f"(d[14]), "=f"(d[15])
    : "r"(a[0]), "r"(a[1]), "r"(a[2]), "r"(a[3]), "l"(db), "n"(TB));
}
template <int TB> __device__ __forceinline__ void wg_rs0_64(float* d, const uint32_t* a, uint64_t db) {
  asm volatile("{wgmma.mma_async.sync.aligned.m64n64k16.f32.bf16.bf16 "
    "{%0,%1,%2,%3,%4,%5,%6,%7,%8,%9,%10,%11,%12,%13,%14,%15,%16,%17,%18,%19,%20,%21,%22,%23,%24,%25,%26,%27,%28,%29,%30,%31}, "
    "{%32,%33,%34,%35}, %36, 0, 1, 1, %37;}"
    : "=f"(d[0]), "=f"(d[1]), "=f"(d[2]), "=f"(d[3]), "=f"(d[4]), "=f"(d[5]), "=f"(d[6]), "=f"(d[7]), "=f"(d[8]), "=f"(d[9]), "=f"(d[10]), "=f"(d[11]),
      "=f"(d[12]), "=f"(d[13]), "=f"(d[14]), "=f"(d[15]), "=f"(d[16]), "=f"(d[17]), "=f"(d[18]), "=f"(d[19]), "=f"(d[20]), "=f"(d[21]), "=f"(d[22]), "=f"(d[23]),
      "=f"(d[24]), "=f"(d[25]), "=f"(d[26]), "=f"(d[27]), "=f"(d[28]), "=f"(d[29]), "=f"(d[30]), "=f"(d[31])
    : "r"(a[0]), "r"(a[1]), "r"(a[2]), "r"(a[3]), "l"(db), "n"(TB));
}
template <int TB> __device__ __forceinline__ void wg_rs0_192(float* d, const uint32_t* a, uint64_t db) {
  asm volatile("{wgmma.mma_async.sync.aligned.m64n192k16.f32.bf16.bf16 "
    "{%0,%1,%2,%3,%4,%5,%6,%7,%8,%9,%10,%11,%12,%13,%14,%15,%16,%17,%18,%19,%20,%21,%22,%23,%24,%25,%26,%27,%28,%29,%30,%31,%32,%33,%34,%35,%36,%37,%38,%39,%40,%41,%42,%43,%44,%45,%46,%47,%48,%49,%50,%51,%52,%53,%54,%55,%56,%57,%58,%59,%60,%61,%62,%63,%64,%65,%66,%67,%68,%69,%70,%71,%72,%73,%74,%75,%76,%77,%78,%79,%80,%81,%82,%83,%84,%85,%86,%87,%88,%89,%90,%91,%92,%93,%94,%95}, "
    "{%96,%97,%98,%99}, %100, 0, 1, 1, %101;}"
    : "=f"(d[0]), "=f"(d[1]), "=f"(d[2]), "=f"(d[3]), "=f"(d[4]), "=f"(d[5]), "=f"(d[6]), "=f"(d[7]), "=f"(d[8]), "=f"(d[9]), "=f"(d[10]), "=f"(d[11]),
      "=f"(d[12]), "=f"(d[13]), "=f"(d[14]), "=f"(d[15]), "=f"(d[16]), "=f"(d[17]), "=f"(d[18]), "=f"(d[19]), "=f"(d[20]), "=f"(d[21]), "=f"(d[22]), "=f"(d[23]),
      "=f"(d[24]), "=f"(d[25]), "=f"(d[26]), "=f"(d[27]), "=f"(d[28]), "=f"(d[29]), "=f"(d[30]), "=f"(d[31]), "=f"(d[32]), "=f"(d[33]), "=f"(d[34]), "=f"(d[35]),
      "=f"(d[36]), "=f"(d[37]), "=f"(d[38]), "=f"(d[39]), "=f"(d[40]), "=f"(d[41]), "=f"(d[42]), "=f"(d[43]), "=f"(d[44]), "=f"(d[45]), "=f"(d[46]), "=f"(d[47]),
      "=f"(d[48]), "=f"(d[49]), "=f"(d[50]), "=f"(d[51]), "=f"(d[52]), "=f"(d[53]), "=f"(d[54]), "=f"(d[55]), "=f"(d[56]), "=f"(d[57]), "=f"(d[58]), "=f"(d[59]),
      "=f"(d[60]), "=f"(d[61]), "=f"(d[62]), "=f"(d[63]), "=f"(d[64]), "=f"(d[65]), "=f"(d[66]), "=f"(d[67]), "=f"(d[68]), "=f"(d[69]), "=f"(d[70]), "=f"(d[71]),
      "=f"(d[72]), "=f"(d[73]), "=f"(d[74]), "=f"(d[75]), "=f"(d[76]), "=f"(d[77]), "=f"(d[78]), "=f"(d[79]), "=f"(d[80]), "=f"(d[81]), "=f"(d[82]), "=f"(d[83]),
      "=f"(d[84]), "=f"(d[85]), "=f"(d[86]), "=f"(d[87]), "=f"(d[88]), "=f"(d[89]), "=f"(d[90]), "=f"(d[91]), "=f"(d[92]), "=f"(d[93]), "=f"(d[94]), "=f"(d[95])
    : "r"(a[0]), "r"(a[1]), "r"(a[2]), "r"(a[3]), "l"(db), "n"(TB));
}
template <int N, int TB> __device__ __forceinline__ void wg_rs0(float* d, const uint32_t* a, uint64_t db) {
  if constexpr (N == 32) wg_rs0_32<TB>(d, a, db);
  if constexpr (N == 64) wg_rs0_64<TB>(d, a, db);
  if constexpr (N == 192) wg_rs0_192<TB>(d, a, db);
}
template <int TB> __device__ __forceinline__ void wg_rs_8(float* d, const uint32_t* a, uint64_t db, int sd) {
  asm volatile("{.reg .pred p; setp.ne.b32 p, %9, 0; wgmma.mma_async.sync.aligned.m64n8k16.f32.bf16.bf16 "
    "{%0,%1,%2,%3}, "
    "{%4,%5,%6,%7}, %8, p, 1, 1, %10;}"
    : "+f"(d[0]), "+f"(d[1]), "+f"(d[2]), "+f"(d[3])
    : "r"(a[0]), "r"(a[1]), "r"(a[2]), "r"(a[3]), "l"(db), "r"(sd), "n"(TB));
}
template <int TB> __device__ __forceinline__ void wg_rs_16(float* d, const uint32_t* a, uint64_t db, int sd) {
  asm volatile("{.reg .pred p; setp.ne.b32 p, %13, 0; wgmma.mma_async.sync.aligned.m64n16k16.f32.bf16.bf16 "
    "{%0,%1,%2,%3,%4,%5,%6,%7}, "
    "{%8,%9,%10,%11}, %12, p, 1, 1, %14;}"
    : "+f"(d[0]), "+f"(d[1]), "+f"(d[2]), "+f"(d[3]), "+f"(d[4]), "+f"(d[5]), "+f"(d[6]), "+f"(d[7])
    : "r"(a[0]), "r"(a[1]), "r"(a[2]), "r"(a[3]), "l"(db), "r"(sd), "n"(TB));
}
template <int TB> __device__ __forceinline__ void wg_rs_24(float* d, const uint32_t* a, uint64_t db, int sd) {
  asm volatile("{.reg .pred p; setp.ne.b32 p, %17, 0; wgmma.mma_async.sync.aligned.m64n24k16.f32.bf16.bf16 "
    "{%0,%1,%2,%3,%4,%5,%6,%7,%8,%9,%10,%11}, "
    "{%12,%13,%14,%15}, %16, p, 1, 1, %18;}"
    : "+f"(d[0]), "+f"(d[1]), "+f"(d[2]), "+f"(d[3]), "+f"(d[4]), "+f"(d[5]), "+f"(d[6]), "+f"(d[7]), "+f"(d[8]), "+f"(d[9]), "+f"(d[10]), "+f"(d[11])
    : "r"(a[0]), "r"(a[1]), "r"(a[2]), "r"(a[3]), "l"(db), "r"(sd), "n"(TB));
}
template <int TB> __device__ __forceinline__ void wg_rs_32(float* d, const uint32_t* a, uint64_t db, int sd) {
  asm volatile("{.reg .pred p; setp.ne.b32 p, %21, 0; wgmma.mma_async.sync.aligned.m64n32k16.f32.bf16.bf16 "
    "{%0,%1,%2,%3,%4,%5,%6,%7,%8,%9,%10,%11,%12,%13,%14,%15}, "
    "{%16,%17,%18,%19}, %20, p, 1, 1, %22;}"
    : "+f"(d[0]), "+f"(d[1]), "+f"(d[2]), "+f"(d[3]), "+f"(d[4]), "+f"(d[5]), "+f"(d[6]), "+f"(d[7]), "+f"(d[8]), "+f"(d[9]), "+f"(d[10]), "+f"(d[11]),
      "+f"(d[12]), "+f"(d[13]), "+f"(d[14]), "+f"(d[15])
    : "r"(a[0]), "r"(a[1]), "r"(a[2]), "r"(a[3]), "l"(db), "r"(sd), "n"(TB));
}
template <int TB> __device__ __forceinline__ void wg_rs_40(float* d, const uint32_t* a, uint64_t db, int sd) {
  asm volatile("{.reg .pred p; setp.ne.b32 p, %25, 0; wgmma.mma_async.sync.aligned.m64n40k16.f32.bf16.bf16 "
    "{%0,%1,%2,%3,%4,%5,%6,%7,%8,%9,%10,%11,%12,%13,%14,%15,%16,%17,%18,%19}, "
    "{%20,%21,%22,%23}, %24, p, 1, 1, %26;}"
    : "+f"(d[0]), "+f"(d[1]), "+f"(d[2]), "+f"(d[3]), "+f"(d[4]), "+f"(d[5]), "+f"(d[6]), "+f"(d[7]), "+f"(d[8]), "+f"(d[9]), "+f"(d[10]), "+f"(d[11]),
      "+f"(d[12]), "+f"(d[13]), "+f"(d[14]), "+f"(d[15]), "+f"(d[16]), "+f"(d[17]), "+f"(d[18]), "+f"(d[19])
    : "r"(a[0]), "r"(a[1]), "r"(a[2]), "r"(a[3]), "l"(db), "r"(sd), "n"(TB));
}
template <int TB> __device__ __forceinline__ void wg_rs_48(float* d, const uint32_t* a, uint64_t db, int sd) {
  asm volatile("{.reg .pred p; setp.ne.b32 p, %29, 0; wgmma.mma_async.sync.aligned.m64n48k16.f32.bf16.bf16 "
    "{%0,%1,%2,%3,%4,%5,%6,%7,%8,%9,%10,%11,%12,%13,%14,%15,%16,%17,%18,%19,%20,%21,%22,%23}, "
    "{%24,%25,%26,%27}, %28, p, 1, 1, %30;}"
    : "+f"(d[0]), "+f"(d[1]), "+f"(d[2]), "+f"(d[3]), "+f"(d[4]), "+f"(d[5]), "+f"(d[6]), "+f"(d[7]), "+f"(d[8]), "+f"(d[9]), "+f"(d[10]), "+f"(d[11]),
      "+f"(d[12]), "+f"(d[13]), "+f"(d[14]), "+f"(d[15]), "+f"(d[16]), "+f"(d[17]), "+f"(d[18]), "+f"(d[19]), "+f"(d[20]), "+f"(d[21]), "+f"(d[22]), "+f"(d[23])
    : "r"(a[0]), "r"(a[1]), "r"(a[2]), "r"(a[3]), "l"(db), "r"(sd), "n"(TB));
}
template <int TB> __device__ __forceinline__ void wg_rs_56(float* d, const uint32_t* a, uint64_t db, int sd) {
  asm volatile("{.reg .pred p; setp.ne.b32 p, %33, 0; wgmma.mma_async.sync.aligned.m64n56k16.f32.bf16.bf16 "
    "{%0,%1,%2,%3,%4,%5,%6,%7,%8,%9,%10,%11,%12,%13,%14,%15,%16,%17,%18,%19,%20,%21,%22,%23,%24,%25,%26,%27}, "
    "{%28,%29,%30,%31}, %32, p, 1, 1, %34;}"
    : "+f"(d[0]), "+f"(d[1]), "+f"(d[2]), "+f"(d[3]), "+f"(d[4]), "+f"(d[5]), "+f"(d[6]), "+f"(d[7]), "+f"(d[8]), "+f"(d[9]), "+f"(d[10]), "+f"(d[11]),
      "+f"(d[12]), "+f"(d[13]), "+f"(d[14]), "+f"(d[15]), "+f"(d[16]), "+f"(d[17]), "+f"(d[18]), "+f"(d[19]), "+f"(d[20]), "+f"(d[21]), "+f"(d[22]), "+f"(d[23]),
      "+f"(d[24]), "+f"(d[25]), "+f"(d[26]), "+f"(d[27])
    : "r"(a[0]), "r"(a[1]), "r"(a[2]), "r"(a[3]), "l"(db), "r"(sd), "n"(TB));
}
template <int TB> __device__ __forceinline__ void wg_rs_64(float* d, const uint32_t* a, uint64_t db, int sd) {
  asm volatile("{.reg .pred p; setp.ne.b32 p, %37, 0; wgmma.mma_async.sync.aligned.m64n64k16.f32.bf16.bf16 "
    "{%0,%1,%2,%3,%4,%5,%6,%7,%8,%9,%10,%11,%12,%13,%14,%15,%16,%17,%18,%19,%20,%21,%22,%23,%24,%25,%26,%27,%28,%29,%30,%31}, "
    "{%32,%33,%34,%35}, %36, p, 1, 1, %38;}"
    : "+f"(d[0]), "+f"(d[1]), "+f"(d[2]), "+f"(d[3]), "+f"(d[4]), "+f"(d[5]), "+f"(d[6]), "+f"(d[7]), "+f"(d[8]), "+f"(d[9]), "+f"(d[10]), "+f"(d[11]),
      "+f"(d[12]), "+f"(d[13]), "+f"(d[14]), "+f"(d[15]), "+f"(d[16]), "+f"(d[17]), "+f"(d[18]), "+f"(d[19]), "+f"(d[20]), "+f"(d[21]), "+f"(d[22]), "+f"(d[23]),
      "+f"(d[24]), "+f"(d[25]), "+f"(d[26]), "+f"(d[27]), "+f"(d[28]), "+f"(d[29]), "+f"(d[30]), "+f"(d[31])
    : "r"(a[0]), "r"(a[1]), "r"(a[2]), "r"(a[3]), "l"(db), "r"(sd), "n"(TB));
}
template <int TB> __device__ __forceinline__ void wg_rs_192(float* d, const uint32_t* a, uint64_t db, int sd) {
  asm volatile("{.reg .pred p; setp.ne.b32 p, %101, 0; wgmma.mma_async.sync.aligned.m64n192k16.f32.bf16.bf16 "
    "{%0,%1,%2,%3,%4,%5,%6,%7,%8,%9,%10,%11,%12,%13,%14,%15,%16,%17,%18,%19,%20,%21,%22,%23,%24,%25,%26,%27,%28,%29,%30,%31,%32,%33,%34,%35,%36,%37,%38,%39,%40,%41,%42,%43,%44,%45,%46,%47,%48,%49,%50,%51,%52,%53,%54,%55,%56,%57,%58,%59,%60,%61,%62,%63,%64,%65,%66,%67,%68,%69,%70,%71,%72,%73,%74,%75,%76,%77,%78,%79,%80,%81,%82,%83,%84,%85,%86,%87,%88,%89,%90,%91,%92,%93,%94,%95}, "
    "{%96,%97,%98,%99}, %100, p, 1, 1, %102;}"
    : "+f"(d[0]), "+f"(d[1]), "+f"(d[2]), "+f"(d[3]), "+f"(d[4]), "+f"(d[5]), "+f"(d[6]), "+f"(d[7]), "+f"(d[8]), "+f"(d[9]), "+f"(d[10]), "+f"(d[11]),
      "+f"(d[12]), "+f"(d[13]), "+f"(d[14]), "+f"(d[15]), "+f"(d[16]), "+f"(d[17]), "+f"(d[18]), "+f"(d[19]), "+f"(d[20]), "+f"(d[21]), "+f"(d[22]), "+f"(d[23]),
      "+f"(d[24]), "+f"(d[25]), "+f"(d[26]), "+f"(d[27]), "+f"(d[28]), "+f"(d[29]), "+f"(d[30]), "+f"(d[31]), "+f"(d[32]), "+f"(d[33]), "+f"(d[34]), "+f"(d[35]),
      "+f"(d[36]), "+f"(d[37]), "+f"(d[38]), "+f"(d[39]), "+f"(d[40]), "+f"(d[41]), "+f"(d[42]), "+f"(d[43]), "+f"(d[44]), "+f"(d[45]), "+f"(d[46]), "+f"(d[47]),
      "+f"(d[48]), "+f"(d[49]), "+f"(d[50]), "+f"(d[51]), "+f"(d[52]), "+f"(d[53]), "+f"(d[54]), "+f"(d[55]), "+f"(d[56]), "+f"(d[57]), "+f"(d[58]), "+f"(d[59]),
      "+f"(d[60]), "+f"(d[61]), "+f"(d[62]), "+f"(d[63]), "+f"(d[64]), "+f"(d[65]), "+f"(d[66]), "+f"(d[67]), "+f"(d[68]), "+f"(d[69]), "+f"(d[70]), "+f"(d[71]),
      "+f"(d[72]), "+f"(d[73]), "+f"(d[74]), "+f"(d[75]), "+f"(d[76]), "+f"(d[77]), "+f"(d[78]), "+f"(d[79]), "+f"(d[80]), "+f"(d[81]), "+f"(d[82]), "+f"(d[83]),
      "+f"(d[84]), "+f"(d[85]), "+f"(d[86]), "+f"(d[87]), "+f"(d[88]), "+f"(d[89]), "+f"(d[90]), "+f"(d[91]), "+f"(d[92]), "+f"(d[93]), "+f"(d[94]), "+f"(d[95])
    : "r"(a[0]), "r"(a[1]), "r"(a[2]), "r"(a[3]), "l"(db), "r"(sd), "n"(TB));
}
template <int N, int TB> __device__ __forceinline__ void wg_rs(float* d, const uint32_t* a, uint64_t db, int sd) {
  if constexpr (N == 8) wg_rs_8<TB>(d, a, db, sd);
  if constexpr (N == 16) wg_rs_16<TB>(d, a, db, sd);
  if constexpr (N == 24) wg_rs_24<TB>(d, a, db, sd);
  if constexpr (N == 32) wg_rs_32<TB>(d, a, db, sd);
  if constexpr (N == 40) wg_rs_40<TB>(d, a, db, sd);
  if constexpr (N == 48) wg_rs_48<TB>(d, a, db, sd);
  if constexpr (N == 56) wg_rs_56<TB>(d, a, db, sd);
  if constexpr (N == 64) wg_rs_64<TB>(d, a, db, sd);
  if constexpr (N == 192) wg_rs_192<TB>(d, a, db, sd);
}
template <int N, int TB> __device__ __forceinline__ void wg_mma(float* d, const uint32_t* a, uint64_t db, bool first) {
  if (first) wg_rs0<N, TB>(d, a, db); else wg_rs<N, TB>(d, a, db, 1);
}

template <int V> struct IntC { static constexpr int value = V; };
template <int I, int N, class F> __device__ __forceinline__ void static_for(F&& f) {
  if constexpr (I < N) { f(IntC<I>()); static_for<I + 1, N>(f); }
}
struct Moments { float s[2][2], q[2][2]; };
__device__ __forceinline__ void add_moments(Moments& m, const uint32_t* x, bool first = false) {
#pragma unroll
  for (int k = 0; k < 4; k++) {
    const float lo = blo(x[k]), hi = bhi(x[k]);
    if (first && k < 2) { m.s[k][0] = lo; m.q[k][0] = lo * lo; m.s[k][1] = hi; m.q[k][1] = hi * hi; continue; }
    m.s[k & 1][0] += lo; m.q[k & 1][0] = fmaf(lo, lo, m.q[k & 1][0]);
    m.s[k & 1][1] += hi; m.q[k & 1][1] = fmaf(hi, hi, m.q[k & 1][1]);
  }
}
__device__ __forceinline__ void finish_moments(const Moments& m, uint32_t red, int bar, int w, int lane, float* rs, float* nb) {
  const float s0 = m.s[0][0] + m.s[0][1], s1 = m.s[1][0] + m.s[1][1], q0 = m.q[0][0] + m.q[0][1], q1 = m.q[1][0] + m.q[1][1];
  const bool b0 = lane & 1, b1 = lane & 2;
  const float s = (b0 ? s1 : s0) + __shfl_xor_sync(0xffffffffu, b0 ? s0 : s1, 1);
  const float q = (b0 ? q1 : q0) + __shfl_xor_sync(0xffffffffu, b0 ? q0 : q1, 1);
  float a = (b1 ? q : s) + __shfl_xor_sync(0xffffffffu, b1 ? s : q, 2);
  a += __shfl_xor_sync(0xffffffffu, a, 16);
  sts32(red + w * 64 + (lane & 15) * 4, __float_as_uint(a));
  asm volatile("bar.sync %0, 128;" ::"r"(bar) : "memory");
  uint32_t v[4][4];
#pragma unroll
  for (int k = 0; k < 4; k++) lds128(v[k], red + k * 64 + (lane & 12) * 4);
#pragma unroll
  for (int rw = 0; rw < 2; rw++) {
    const float mean = ((__uint_as_float(v[0][rw]) + __uint_as_float(v[1][rw])) + (__uint_as_float(v[2][rw]) + __uint_as_float(v[3][rw]))) * (1.f / 448.f);
    const float sq = (__uint_as_float(v[0][2 + rw]) + __uint_as_float(v[1][2 + rw])) + (__uint_as_float(v[2][2 + rw]) + __uint_as_float(v[3][2 + rw]));
    const float var = fmaxf(fmaf(sq, 1.f / 448.f, -mean * mean), 0.f);
    asm("rsqrt.approx.ftz.f32 %0, %1;" : "=f"(rs[rw]) : "f"(var + 1e-5f));
    nb[rw] = -mean;
  }
}

template <class F>
__device__ __forceinline__ void conv_half(F&& chores, uint4* g_Y, const int HI, uint32_t sb, uint32_t bars, int w, int lane, int quad, uint32_t tag, uint32_t zero, int& budget) {
  const int t = lane & 3, g0 = (lane >> 2) & 1, o = lane >> 3, a = (~t >> 1) & 1, b = ~t & 1;
  uint32_t fo = sb + OFF_TAB + 32 + 4 * (8 * o + 2 * w + g0 - 2 * t);
  uint32_t tb = bars + 8 * B_TAB;
  uint64_t dB = mkdesc(sb + OFF_SSM, SSM_PL, HI_NONE, zero);
  const uint32_t zv = zero & lane;
  const int lm = (lane - 8) & 31;
  const int src_h1 = lm, src_h0 = o > 0 ? lm : lm ^ 2, src2 = (lane ^ 17) ^ ((b && o >= 2) ? 2 : 0);
  const bool o3 = o == 3, o3a = o3 && a, sw = !b || o >= 2, prv = b && o >= 2 && a;
  const int tl = (o ^ (b ? 2 : 0)) + (b ? 0 : 4) + 8 * (a ^ ((b && o >= 2) ? 1 : 0));
  uint4* yp = g_Y + ((HI * 128 + 2 * tl + (w >> 1)) * 448 + quad * 4 + 2 * (w & 1) + g0);
  float acc[4][32];
  uint32_t fa[2][2][4][4], yk[2], y1[2], c1[2], c2[2], sv[2][4];
  const uint32_t spill = sb + OFF_H + STG_TILE + STG_HALF + (w * 32 + lane) * 16;
  auto ld = [&](auto d_) {
    constexpr int D = decltype(d_)::value;
    mbar_wait(tb + 8 * D, 0);
#pragma unroll
    for (int k = 0; k < 2; k++)
#pragma unroll
      for (int ch = 0; ch < 4; ch++) {
        fa[D & 1][k][ch][0] = lds32(fo + ch * TAB_PL + 512 * D + 256 * k);
        fa[D & 1][k][ch][1] = lds32(fo + ch * TAB_PL + 512 * D + 256 * k + 128);
      }
  };
  auto fold2 = [&](const uint32_t* d, uint32_t p1, uint32_t p2) {
    const uint32_t s0 = badd2(d[1], __shfl_sync(0xffffffffu, o3a ? p1 : (o3 ? d[2] : d[0]), src_h0));
    const uint32_t keep = sw ? d[3] : s0;
    return badd2(prv ? p2 : keep, __shfl_sync(0xffffffffu, sw ? s0 : d[3], src2));
  };
  auto fold = [&](auto i_) {
    constexpr int I = decltype(i_)::value;
    uint32_t y[2];
#pragma unroll
    for (int cp = 0; cp < 2; cp++) {
      float* da = acc[2 * cp] + 4 * (7 - I);
      float* db = acc[2 * cp + 1] + 4 * (7 - I);
      pin<4>(da);
      pin<4>(db);
      uint32_t d[4] = {pack2(da[0], db[0]), pack2(da[1], db[1]), pack2(da[2], db[2]), pack2(da[3], db[3])};
      d[3] = badd2(d[3], __shfl_sync(0xffffffffu, o3 ? d[0] : d[2], src_h1));
      if (I > 0) y[cp] = fold2(d, c1[cp], c2[cp]);
      else { sv[cp][0] = d[0]; sv[cp][1] = d[1]; sv[cp][2] = d[2]; sv[cp][3] = d[3]; }
      c1[cp] = d[2];
      c2[cp] = d[3];
    }
    if (I == 1) {
      y1[0] = y[0]; y1[1] = y[1];
    } else if (I > 1) {
      if (!(I & 1)) {
        yk[0] = tagged(bmul2(y[0], P_DOWN2), tag);
        yk[1] = y[1];
      } else {
        ll_st(yp + (I >> 1) * (32 * 448), yk[0], yk[1], y[0], y[1]);
      }
    }
  };
  auto copies = [&](auto d_, bool first) {
    constexpr int D = decltype(d_)::value;
#pragma unroll
    for (int ch = 0; ch < 4; ch++) {
      uint32_t(*f)[4][4] = fa[D & 1];
      f[0][ch][2] = first ? f[0][ch][1] & zv : fa[~D & 1][1][ch][1] ^ (f[0][ch][1] & zv);
      f[0][ch][3] = f[0][ch][0] ^ zv;
      f[1][ch][2] = f[0][ch][1] ^ zv;
      f[1][ch][3] = f[1][ch][0] ^ zv;
    }
  };
  auto fin0 = [&]() {
    uint32_t cin[4] = {0, 0, 0, 0};
    if (HI) { mbar_wait(bars + 8 * B_SPILL, 0); lds128(cin, spill); }
    ll_st(yp, tagged(bmul2(fold2(sv[0], cin[0], cin[2]), P_DOWN2), tag), fold2(sv[1], cin[1], cin[3]), y1[0], y1[1]);
  };
  auto step = [&](auto d_) {
    constexpr int D = decltype(d_)::value, d = D - 8;
    constexpr int N = d < 0 ? 64 : 64 - 8 * d;
    if (D != 8) pinu<32>(fa[D & 1][0][0]);
    WG_FENCE();
#pragma unroll
    for (int k = 0; k < 2; k++)
#pragma unroll
      for (int ch = 0; ch < 4; ch++) wg_mma<N, 0>(acc[ch], fa[D & 1][k][ch], dB + ((ch * SSM_CH) >> 4) + 8 * D + 4 * k, false);
    WG_COMMIT();
    if constexpr (d == 0 || d == 1) ll_st(yp + (2 + d) * (32 * 448), 0, 0, 0, 0);
    if constexpr (d >= 0) chores(IntC<d>());
    if constexpr (D < 15) {
      WG_WAIT(1);
      ld(IntC<D + 1>());
      if constexpr (d >= 1) fold(IntC<d - 1>());
      if constexpr (d == 4) fin0();
      copies(IntC<D + 1>(), false);
    }
  };
#pragma unroll
  for (int ch = 0; ch < 4; ch++)
#pragma unroll
    for (int i = 0; i < 32; i++) acc[ch][i] = 0.f;
  ld(IntC<0>());
  copies(IntC<0>(), true);
  const uint64_t dB0 = dB;
#pragma unroll 1
  for (int it = 4 * HI; it > 0; it--) {
#pragma unroll
    for (int ch = 0; ch < 4; ch++) pin<32>(acc[ch]);
    static_for<0, 2>(step);
    WG_WAIT(0);
    fo += 1024;
    tb += 16;
    dB += 16;
  }
  fo -= 4096;
  tb -= 64;
  dB = dB0;
#pragma unroll
  for (int ch = 0; ch < 4; ch++) pin<32>(acc[ch]);
  static_for<8, 16>(step);
  if (HI) turn_give(2);
  WG_WAIT(1);
  fold(IntC<6>());
  WG_WAIT(0);
  fold(IntC<7>());
  if (!HI) { sts128(spill, c1[0], c1[1], c2[0], c2[1]); warp_arrive(bars + 8 * B_SPILL, lane); }
}

__global__ void __cluster_dims__(2, 1, 1) __launch_bounds__(NTHREADS, 1)
h3ffn_kernel(const __nv_bfloat16* __restrict__ ssmk, const __nv_bfloat16* __restrict__ ssmD, const __nv_bfloat16* __restrict__ shiftk,
             unsigned* g_epoch, const __nv_bfloat16* __restrict__ kin, const __nv_bfloat16* __restrict__ vin, const uint32_t zero,
             uint4* g_Y, uint4* g_X, uint4* g_P, const __nv_bfloat16* __restrict__ q, const __nv_bfloat16* __restrict__ w1,
             const __nv_bfloat16* __restrict__ w2, __nv_bfloat16* __restrict__ out,
             const __grid_constant__ CUtensorMap tmK, const __grid_constant__ CUtensorMap tmV,
             const __grid_constant__ CUtensorMap tmW1m, const __grid_constant__ CUtensorMap tmW1t,
             const __grid_constant__ CUtensorMap tmW2m, const __grid_constant__ CUtensorMap tmW2t) {
  extern __shared__ __align__(1024) unsigned char smem_raw[];
  const uint32_t sb = (uint32_t)__cvta_generic_to_shared(smem_raw);
  const uint32_t bars = sb + OFF_BAR;
  const int tid = threadIdx.x, lane = tid & 31;
  const int warp = __shfl_sync(0xffffffffu, tid >> 5, 0), wg = warp >> 2;
  const int cl = blockIdx.x >> 1, r = blockIdx.x & 1;
  const int c7 = ((cl - 36) * 37) >> 8;
  const int gpc = cl < 4 ? 0 : cl < 36 ? (cl - 4) & 7 : cl - 35 - 7 * c7, idx = cl < 4 ? 4 + cl : cl < 36 ? (cl - 4) >> 3 : 4 + c7;
  const int ps = gpc >> 1, gi = (gpc & 1) * 8 + idx;
  const bool conv = idx < 7;
  const int cc = idx * 8 + gpc, quad = 2 * cc + r;
  const int own = gi * 8 + 2 * ps + r;
  const int tok0 = 256 * (own >> 5) + 4 * (own & 31);
  int budget = 1 << 18;
  auto kv_load = [&](int i) {
    const uint32_t b = bars + 8 * (B_KV + i), dst = sb + OFF_KV + i * KV_BLK;
    tma3(&tmK, dst, b, cc * 8, (2 * i + r) * 32 - 1, 0);
    tma3(&tmV, dst + KV_HALF, b, cc * 8, (2 * i + r) * 32 - 1, 0);
  };
  if (wg == 2) {
    if (elect()) {
      mbar_init(bars + 8 * (B_KV + warp - 8), 1);
      mbar_expect(bars + 8 * (B_KV + warp - 8), KV_BYTES);
      if (conv && warp == 8) kv_load(0);
    }
  } else if (warp == 4 && lane < 28) {
    asm volatile("prefetch.global.L2 [%0];" ::"l"((lane < 14 ? kin : vin) + (blockIdx.x * 14 + lane % 14) * 64) : "memory");
  }
  if (wg == 2) {
    const int ht = tid - 256, wv = warp - 8;
    const int cp = 2 * (lane >> 4) + (lane & 1), rq = 8 * wv + ((lane >> 1) & 7);
    uint4 skw;
    if (conv) skw = __ldg(reinterpret_cast<const uint4*>(shiftk + cc * 32) + cp);
    auto q_load = [&]() {
#pragma unroll
      for (int k = 0; k < 4; k++)
        bulk_g2s(sb + OFF_H + (wv >> 1) * STG_TILE + (2 * k + (wv & 1)) * STG_PITCH, q + (size_t)((wv >> 1) * 1024 + (wv & 1) * 128 + tok0 + k) * D_, 896, bars + 8 * B_Q);
    };
    auto w1_load = [&](int hs) {
      const uint32_t b = bars + 8 * (B_WFULL + (hs >> 1)), dst = sb + hs * 14336;
      const int row = hs < 7 ? 32 * hs : (hs < 13 ? 32 * hs + 32 : 224);
      tma3(&tmW1m, dst, b, 0, row, 7 * ps + 4 * r);
      tma2(&tmW1t, dst + 12288, b, 448 * ps + 192 + 32 * r, row);
    };
    auto w_prefetch = [&]() {
      asm volatile("cp.async.bulk.prefetch.L2.global [%0], %1;" ::"l"(w1 + (size_t)blockIdx.x * 6272), "r"(12544) : "memory");
      asm volatile("cp.async.bulk.prefetch.L2.global [%0], %1;" ::"l"(w2 + (size_t)blockIdx.x * 6272), "r"(12544) : "memory");
    };
    auto q_stats = [&](int tl) {
      const int row = 2 * wv + (lane >> 4);
      const uint32_t qa = sb + OFF_H + tl * STG_TILE + row * STG_PITCH + (lane & 15) * 8;
      uint32_t x[7][2];
#pragma unroll
      for (int k = 0; k < 7; k++) lds64(x[k], qa + k * 128);
      float s0 = 0.f, s1 = 0.f, q0 = 0.f, q1 = 0.f;
#pragma unroll
      for (int k = 0; k < 14; k++) {
        const float lo = blo(x[k >> 1][k & 1]), hi = bhi(x[k >> 1][k & 1]);
        s0 += lo; q0 = fmaf(lo, lo, q0); s1 += hi; q1 = fmaf(hi, hi, q1);
      }
      s0 += s1; q0 += q1;
#pragma unroll
      for (int k = 1; k < 16; k *= 2) { s0 += __shfl_xor_sync(0xffffffffu, s0, k); q0 += __shfl_xor_sync(0xffffffffu, q0, k); }
      const float mean = s0 * (1.f / 448.f), var = fmaxf(fmaf(q0, 1.f / 448.f, -mean * mean), 0.f);
      float rstd;
      asm("rsqrt.approx.ftz.f32 %0, %1;" : "=f"(rstd) : "f"(var + 1e-5f));
      sts64(sb + OFF_RED + tl * 512 + row * 8, __float_as_uint(rstd), __float_as_uint(-mean));
      warp_arrive(bars + 8 * (B_QST + tl), lane);
    };
    if (elect()) {
      mbar_init(bars + 8 * (B_KV + 4 + wv), 1);
      mbar_init(bars + 8 * (B_HFREE + wv), 4);
      mbar_init(bars + 8 * (B_HFREE + 4 + wv), 4);
      mbar_expect(bars + 8 * (B_KV + 4 + wv), KV_BYTES);
      asm volatile("fence.mbarrier_init.release.cluster;" ::: "memory");
    }
    __syncwarp();
    asm volatile("barrier.cluster.arrive.relaxed.aligned;" ::: "memory");
    asm volatile("setmaxnreg.dec.sync.aligned.u32 %0;" ::"n"(REG_H));
    if (elect()) asm volatile("prefetch.tensormap [%0];" ::"l"(wv == 0 ? &tmW1m : wv == 1 ? &tmW1t : wv == 2 ? &tmW2m : &tmW2t) : "memory");
    if (conv && wv >= 1 && wv < KV_AHEAD) {
      __nanosleep(100);
      if (elect()) kv_load(wv);
    }
    if (conv) {
      const uint32_t sk[4] = {prmt(skw.x, skw.z, 0x5410), prmt(skw.x, skw.z, 0x7632), prmt(skw.y, skw.w, 0x5410), prmt(skw.y, skw.w, 0x7632)};
      asm volatile("barrier.cluster.wait.aligned;" ::: "memory");
      const uint32_t tdst = mapa(sb + OFF_TAB + 2 * (lane & 1) * TAB_PL + 32 + 16 * rq + 512 * r, lane >> 4);
      const uint32_t bdst = mapa(bars + 8 * (B_TAB + r), lane >> 4);
#pragma unroll 1
      for (int i = 0; i < 8; i++) {
        mbar_wait(bars + 8 * (B_KV + i), 0);
        if (i + KV_AHEAD < 8 && wv == 2 + (i & 1) && elect()) kv_load(i + KV_AHEAD);
        const uint32_t ka = sb + OFF_KV + i * KV_BLK + rq * 16 + cp * 4;
        uint32_t kk[8], u[5];
#pragma unroll
        for (int d = 0; d < 8; d++) kk[d] = lds32(ka + (d & 3) * 528 + (d >> 2) * 16);
#pragma unroll
        for (int d = 0; d < 5; d++) u[d] = lds32(ka + KV_HALF + ((d + 3) & 3) * 528 + ((d + 3) >> 2) * 16);
#pragma unroll
        for (int d = 0; d < 5; d++)
          u[d] = bmul2(bfma2(kk[d + 3], sk[0], bfma2(kk[d + 2], sk[1], bfma2(kk[d + 1], sk[2], bmul2(kk[d], sk[3])))), u[d]);
#pragma unroll
        for (int e = 0; e < 2; e++) {
          const uint32_t sel = e ? 0x7632 : 0x5410;
          st_async128(tdst + e * TAB_PL + i * 1024, prmt(u[1], u[0], sel), prmt(u[2], u[1], sel), prmt(u[3], u[2], sel), prmt(u[4], u[3], sel), bdst + 16 * i);
        }
        if (i == 4 && elect()) q_load();
        if (i >= 4 && (wv >> 1) == (i & 1) && elect()) w1_load(2 * (i - 4) + (wv & 1));
      }
      warp_arrive(bars + 8 * B_CFREE0, lane);
    } else {
      asm volatile("barrier.cluster.wait.aligned;" ::: "memory");
      __nanosleep(1500);
      if (elect()) q_load();
      __nanosleep(1500);
    }
    mbar_wait(bars + 8 * B_Q, 0);
#pragma unroll 1
    for (int tl = 0; tl < 2; tl++) {
      if (tl == 1 && wv == 1 && elect()) w_prefetch();
      q_stats(tl);
    }
    if (wv >= 2) {
      const uint32_t tagY = mktag(g_epoch[blockIdx.x]);
#pragma unroll 1
      for (int tl = 0; tl < 2; tl++) {
        if (tl == 0) mbar_wait(bars + 8 * (B_WEMPTY + 6), 0);
        const int c0 = ht - 64;
        uint32_t raw[7][4];
#pragma unroll
        for (int k = 0; k < 7; k++) ll_ld(raw[k], g_Y + ((tl * 128 + own) * 448 + c0) + 64 * k);
        mbar_wait(bars + 8 * B_HCONS, 0);
#pragma unroll
        for (int k = 0; k < 7; k++) {
          const int qd = 16 * k + (c0 >> 2);
          const uint32_t a = sb + OFF_H + tl * STG_TILE + STG_HALF + 2 * (lane & 3) * STG_PITCH + qd * 8 + (qd >= 56 ? 16 : 0);
          sts64(a, raw[k][0] + (P_UP - tagY), raw[k][1]);
          sts64(a + STG_PITCH, raw[k][2], raw[k][3]);
        }
        __syncwarp();
        if (lane < 2) mbar_arrive(bars + 8 * (B_YRDY + tl));
      }
    }
    if (wv < 2 && elect()) {
#pragma unroll 1
      for (int j = (conv ? 4 : 0) + wv; j < 7; j += 2) {
        if (conv && j >= 4) mbar_wait(bars + 8 * (j == 4 ? B_CFREE0 : B_CFREE1), 0);
        if (j >= 5) mbar_wait(bars + 8 * B_G1S, 0);
        w1_load(2 * j);
        w1_load(2 * j + 1);
      }
#pragma unroll 1
      for (int ph = 1; ph < 4; ph++) {
#pragma unroll 1
        for (int j = wv; j < 7; j += 2) {
          const uint32_t b = bars + 8 * (B_WFULL + j), dst = sb + j * SLOT;
          mbar_wait(bars + 8 * (B_WEMPTY + j), (ph - 1) & 1);
          mbar_expect(b, SLOT);
          if (ph == 2) {
            w1_load(2 * j);
            w1_load(2 * j + 1);
          } else if (j > 0) {
            tma2(&tmW2m, dst, b, 256 * r + 64 * ((j - 1) >> 1), 448 * ps + 224 * (((j - 1) & 1) ^ r));
          } else {
            tma2(&tmW2t, dst, b, 192 + 32 * r, 448 * ps + 224 * r);
            tma2(&tmW2t, dst + 14336, b, 192 + 32 * r, 448 * ps + 224 * (r ^ 1));
          }
        }
      }
    }
  } else {
    const int w = warp & 3, wt = tid & 127, tile = wg;
    const uint32_t epoch = g_epoch[blockIdx.x];
    uint4 hw[4];
    uint2 dd;
    auto h_load = [&]() {
#pragma unroll
      for (int ch = 0; ch < 4; ch++) hw[ch] = __ldg(reinterpret_cast<const uint4*>(ssmk + (size_t)(quad * 4 + ch) * S_) + tid);
      dd = __ldg(reinterpret_cast<const uint2*>(ssmD + quad * 4));
    };
    if (conv && wg == 0) {
      h_load();
      sts32(sb + OFF_SSM + (tid >> 4) * SSM_PL + 2048 + (tid & 15) * 4, 0);
      if (tid < 32) sts32(sb + OFF_TAB + (lane >> 3) * TAB_PL + (lane & 7) * 4, 0);
    }
    if (elect()) {
      const uint32_t b = bars + 32 * warp, cn = warp < 6 ? 1 : 4;
      mbar_init(b, cn); mbar_init(b + 8, cn); mbar_init(b + 16, cn); mbar_init(b + 24, warp == 7 ? 8 : cn);
      if (wg == 0) { mbar_expect(b, 2048); mbar_expect(b + 8, 2048); mbar_expect(b + 16, 2048); mbar_expect(b + 24, 2048); }
      if (warp == 4 || warp == 5) { mbar_expect(b, SLOT); mbar_expect(b + 8, SLOT); mbar_expect(b + 16, SLOT); mbar_expect(b + 24, warp == 4 ? SLOT : 14336); }
#pragma unroll
      for (int k = 0; k < 2; k++) { mbar_init(bars + 8 * (B_HFULL + 2 * warp + k), 1); mbar_expect(bars + 8 * (B_HFULL + 2 * warp + k), 4096); }
      mbar_init(bars + 8 * (B_QST + warp), 4);
      asm volatile("fence.mbarrier_init.release.cluster;" ::: "memory");
    }
    __syncwarp();
    asm volatile("barrier.cluster.arrive.relaxed.aligned;" ::: "memory");
    asm volatile("setmaxnreg.inc.sync.aligned.u32 %0;" ::"n"(REG_M));
    auto warm = [&](int n) {
      float d[32];
      uint32_t a[4] = {zero, zero, zero, zero};
#pragma unroll 1
      for (int k = 0; k < n; k++) {
        pinu<4>(a);
        WG_FENCE();
        wg_mma<64, 1>(d, a, mkdesc(sb, 0, HI_128, zero), true);
        WG_COMMIT();
        WG_WAIT(0);
        pin<32>(d);
        if (zero) sts32(sb, __float_as_uint(d[0]));
        if (n > 1) __nanosleep(130);
      }
    };
    if (conv) {
      if (wg == 1) {
        __nanosleep(100);
        h_load();
        warm(3);
      }
#pragma unroll
      for (int ch = 0; ch < 4; ch++) {
        const uint32_t d2 = ch < 2 ? dd.x : dd.y;
        if (tid == 0) hw[ch].x = prmt(badd2(hw[ch].x, (ch & 1) ? d2 >> 16 : d2), hw[ch].x, 0x7610);
        sts128(sb + OFF_SSM + ch * SSM_CH + ((tid >> 2) & 1) * SSM_PL + (127 - 4 * (tid >> 3) - (tid & 3)) * 16, hw[ch].x, hw[ch].y, hw[ch].z, hw[ch].w);
      }
      asm volatile("fence.proxy.async.shared::cta;" ::: "memory");
    }
    asm volatile("barrier.cluster.wait.aligned;" ::: "memory");
    const uint32_t tagY = mktag(epoch);
    auto chores = [&](auto q_) {
      constexpr int Q = decltype(q_)::value;
      if (Q == 0) {
        uint4* xo = g_X + (((gi * 2 + tile) * 8 + 2 * ps + r) * 448 + ((lane >> 4) * 14 + w) * 16 + (lane & 15));
        if (lane < 16) ll_st(xo, 0, 0, 0, 0);
      }
      if (Q >= 2 && Q < 6) {
        uint4* pc = g_P + ((((gi * 2 + tile) * 8 + 2 * w + (lane >> 4)) * 4 + ps) * 448 + r * 224 + (lane & 15));
        ll_st(pc + (6 + Q) * 16, 0, 0, 0, 0);
      }
    };
    if (conv) {
      if (wg == 0) { asm volatile("bar.arrive 1, 256;" ::: "memory"); asm volatile("bar.sync 4, 128;" ::: "memory"); }
      else asm volatile("bar.sync 1, 256;" ::: "memory");
      conv_half(chores, g_Y, wg, sb, bars, w, lane, quad, tagY, zero, budget);
      warp_arrive(bars + 8 * B_CFREE1, lane);
    } else {
      __nanosleep(1500);
      static_for<0, 8>(chores);
      if (wg == 1) turn_give(2);
    }

    auto wfull = [&](int j, uint32_t parity) { if (tile == 0) mbar_wait(bars + 8 * (B_WFULL + j), parity); };
    auto wfull2 = [&](int j, uint32_t parity) { if (tile == 0) mbar_wait2_b(bars + 8 * (B_WFULL + j), parity, budget); };
    auto wfree = [&](int j) { if (tile == 1 && lane == 0) mbar_arrive(bars + 8 * (B_WEMPTY + j)); };
    uint32_t xs[4][4], yw[4][4];
    float rs[2], nb[2];
    const bool full3 = w < 2;
    const uint32_t red = sb + OFF_RED + tile * 512;
#define OWNER_GEOMETRY                                                                                       \
  const uint32_t area = sb + OFF_H + tile * STG_TILE;                                                        \
  const uint32_t col = (lane >> 4) * 512 + w * 32 + (lane & 3) * 4 + ((lane >> 2) & 3) * 2 * STG_PITCH, fix3 = (lane >> 4) * 448; \
  const uint32_t stg = area + STG_HALF + (lane >> 4) * 16 + col;                                             \
  const int blk = (gi * 2 + tile) * 8 + 2 * ps + r, pos = ((lane >> 4) * 14 + w) * 16 + (lane & 15);
    auto yload = [&](uint32_t (*raw)[4], bool again = false) {
      const uint4* yp = g_Y + ((tile * 128 + own) * 448 + (lane >> 4) * 256 + w * 16 + (lane & 1) * 8 + (lane & 2) * 2 + ((lane >> 2) & 3));
#pragma unroll
      for (int p = 0; p < 3; p++) { if (again) ll_retry(raw[p], yp + 64 * p, tagY); else ll_ld(raw[p], yp + 64 * p); }
      if (!again) { raw[3][0] = full3 ? 0 : tagY; raw[3][1] = raw[3][2] = raw[3][3] = 0; }
      ll_retry(raw[3], yp + 192 - (lane >> 4) * 224, tagY);
    };
    auto yswap = [&](uint32_t (*raw)[4]) {
      const bool odd = lane & 1;
#pragma unroll
      for (int p = 0; p < 4; p++) {
        raw[p][0] += P_UP - tagY;
#pragma unroll
        for (int rw = 0; rw < 2; rw++) {
          const uint32_t o = __shfl_xor_sync(0xffffffffu, odd ? raw[p][2 * rw] : raw[p][2 * rw + 1], 1);
          yw[p][rw] = odd ? o : raw[p][2 * rw];
          yw[p][2 + rw] = odd ? raw[p][2 * rw + 1] : o;
          if (p == 3 && !full3) yw[p][rw] = yw[p][2 + rw] = 0;
        }
      }
    };
    auto yread = [&]() {
      OWNER_GEOMETRY
#pragma unroll
      for (int p = 0; p < 4; p++)
#pragma unroll
        for (int k = 0; k < 4; k++) {
          const uint32_t a = stg + (k & 1) * STG_PITCH + 128 * p + 16 * (k >> 1);
          yw[p][k] = p < 3 ? lds32(a) : lds32_if(a - fix3, full3);
        }
      (void)blk; (void)pos;
    };
    auto pload = [&](uint32_t (*raw)[4], int k0, int k1) {
      OWNER_GEOMETRY
      const uint4* pr = g_P + (blk * 1792 + pos);
#pragma unroll
      for (int k = k0; k < k1; k++) {
        if (k < 12) ll_ld(raw[k], pr + (k & 3) * 448 + (k >> 2) * 64);
        else ll_ld_if(raw[k], pr + (k & 3) * 448 + (k >> 2) * 64, full3);
      }
      (void)stg; (void)fix3;
    };
    auto pwait = [&](uint32_t (*raw)[4], int p, uint32_t tagp) {
      OWNER_GEOMETRY
      ll_wait4<448, true>(raw + 4 * p, g_P + (blk * 1792 + pos) + p * 64, tagp, zero, budget);
      (void)stg; (void)fix3;
    };
    auto reduce = [&](auto last_, uint32_t (*raw)[4], uint32_t tagp) {
      constexpr bool LAST = decltype(last_)::value;
      OWNER_GEOMETRY
      Moments m = {};
      auto take = [&](int p) {
#pragma unroll
        for (int k = 0; k < 4; k++) {
          uint32_t s[4];
#pragma unroll
          for (int j = 0; j < 4; j++) s[j] = k ? raw[4 * p + j][k] : raw[4 * p + j][0] + (P_UP - tagp);
          xs[p][k] = badd2(xs[p][k], badd2(badd2(s[0], s[1]), badd2(s[2], s[3])));
        }
        if (LAST) {
          const bool odd = lane & 1;
          char* op = reinterpret_cast<char*>(out) + ((tile * 1024 + tok0 + ((lane >> 2) & 3)) * 896 + (lane >> 4) * 512 + w * 32 + (lane & 1) * 16 + (lane & 2) * 4);
#pragma unroll
          for (int rw = 0; rw < 2; rw++) {
            const uint32_t o = __shfl_xor_sync(0xffffffffu, odd ? xs[p][rw] : xs[p][2 + rw], 1);
            *reinterpret_cast<uint2*>(op + rw * (128 * 896) + 128 * p - (p == 3 ? fix3 : 0)) = odd ? make_uint2(o, xs[p][2 + rw]) : make_uint2(xs[p][rw], o);
          }
        }
        if (!LAST) add_moments(m, xs[p]);
      };
      pwait(raw, 0, tagp);
      if (full3) pwait(raw, 3, tagp);
      if (full3) take(3);
      take(0);
      pinu<4>(xs[0]);
      if (!LAST) pin<8>(&m.s[0][0]);
      sched_fence(zero);
      pload(raw, 4, 12);
      if (!LAST) { mbar_wait(bars + 8 * (B_YRDY + tile), 0); yread(); }
      pwait(raw, 1, tagp);
      take(1);
      pinu<8>(xs[0]);
      if (!LAST) pin<8>(&m.s[0][0]);
      pwait(raw, 2, tagp);
      take(2);
      if (!LAST) {
        pin<8>(&m.s[0][0]);
        finish_moments(m, red, 4 + tile, w, lane, rs, nb);
        pin<2>(rs); pin<2>(nb);
      }
      (void)blk; (void)pos; (void)stg;
    };
    {
      OWNER_GEOMETRY
      uint32_t raw[4][4];
      yload(raw);
      mbar_wait(bars + 8 * (B_QST + tile), 0);
#pragma unroll
      for (int p = 0; p < 4; p++)
#pragma unroll
        for (int k = 0; k < 4; k++) {
          const uint32_t a = area + (k & 1) * STG_PITCH + col + 128 * p + 16 * (k >> 1);
          xs[p][k] = p < 3 ? lds32(a) : lds32_if(a - fix3, full3);
        }
      uint32_t st4[4];
      lds128(st4, red + (lane & 12) * 4);
      rs[0] = __uint_as_float(st4[0]); nb[0] = __uint_as_float(st4[1]); rs[1] = __uint_as_float(st4[2]); nb[1] = __uint_as_float(st4[3]);
      while (ll_bad4(raw, tagY) && --budget > 0) {
        if (!conv) __nanosleep(200);
        yload(raw, true);
      }
      yswap(raw);
      (void)blk; (void)pos; (void)stg;
    }
    uint32_t praw[16][4];
#pragma unroll 1
    for (int layer = 0;; layer++) {
      const uint32_t tag = mktag(2 * epoch + layer);
      {
        OWNER_GEOMETRY
        Moments m = {};
        const uint32_t r2[2] = {pack2(rs[0], rs[0]), pack2(rs[1], rs[1])}, n2[2] = {pack2(nb[0], nb[0]), pack2(nb[1], nb[1])};
#pragma unroll
        for (int p = 0; p < 4; p++) {
#pragma unroll
          for (int k = 0; k < 4; k++) xs[p][k] = bfma2(bmul2(badd2(xs[p][k], n2[k & 1]), r2[k & 1]), yw[p][k], xs[p][k]);
          add_moments(m, xs[p], p == 0);
        }
        pin<8>(&m.s[0][0]);
        finish_moments(m, red + 256, 4 + tile, w, lane, rs, nb);
        pin<2>(rs); pin<2>(nb);
        const uint32_t ra = pack2(rs[0] * 0.5f, rs[1] * 0.5f), na = pack2(nb[0], nb[1]);
        const uint32_t r0 = prmt(ra, ra, 0x1010), r1 = prmt(ra, ra, 0x3232), n0 = prmt(na, na, 0x1010), n1 = prmt(na, na, 0x3232);
        const uint32_t rt = bmul2(r0, 0x3D003D00u);
        uint4* xo = g_X + (blk * 448 + pos);
#pragma unroll
        for (int p = 0; p < 4; p++) {
          if (p < 3 || full3)
            ll_st(xo + p * 64, tagged(bmul2(badd2(xs[p][0], n0), rt), tag), bmul2(badd2(xs[p][1], n1), r1), bmul2(badd2(xs[p][2], n0), r0), bmul2(badd2(xs[p][3], n1), r1));
        }
        if (tile == 1 && lane == 0) mbar_arrive_remote(mapa(bars + 8 * B_HFREE, r ^ 1));
        (void)stg; (void)fix3;
      }
      uint32_t h[28][4];
      {
        const uint4* xp = g_X + (((gi * 2 + tile) * 8 + 2 * w + (lane >> 4)) * 448 + (lane & 15));
        float acc[112];
        uint32_t xr[7][4][4], xa[2][4][4];
        auto xload = [&](int c) {
#pragma unroll
          for (int k = 0; k < 4; k++) ll_ld(xr[c][k], xp + (4 * c + k) * 16);
        };
        auto xtake = [&](int c) {
          if (c > 0) ll_wait4<16, false>(xr[c], xp + 64 * c, tag, zero, budget);
#pragma unroll
          for (int k = 0; k < 4; k++) {
            xa[c & 1][k][0] = xr[c][k][0] + (X_UP - tag);
#pragma unroll
            for (int j = 1; j < 4; j++) xa[c & 1][k][j] = __float_as_uint(__fmul_rn(__uint_as_float(xr[c][k][j]), __uint_as_float(0x3F800000u | zero)));
          }
          pinu<16>(xa[c & 1][0]);
        };
        xload(0);
        if (tile == 0) warm(1);
        ll_wait4<16, true>(xr[0], xp, tag, zero, budget);
        xload(1); xload(2);
        xtake(0);
        wfull(0, 0);
        turn_wait(2 + wg);
        const uint64_t dm = mkdesc(sb, 4096, HI_128, zero), dt = mkdesc(sb + 12288, 0, HI_64, zero);
#pragma unroll
        for (int c = 0; c < 7; c++) {
          WG_FENCE();
#pragma unroll
          for (int k = 0; k < 4; k++) {
            const int s = 4 * c + k;
            wg_mma<192, 1>(acc, xa[c & 1][k], dm + (((s >> 1) * 14336 + (s & 1) * 2048) >> 4), s == 0);
            wg_mma<32, 1>(acc + 96, xa[c & 1][k], dt + (((s >> 1) * 14336 + (s & 1) * 1024) >> 4), s == 0);
          }
          WG_COMMIT();
          if (c == 6) turn_give(3 - wg);
          if (c > 0) {
            WG_WAIT(1);
            wfree(c - 1);
          }
          if (c < 6) {
            wfull(c + 1, 0);
            xtake(c + 1);
            if (c == 0 && tile == 0 && lane == 0) mbar_arrive(bars + 8 * B_G1S);
            if (c == 0 || c == 2) { xload(c + 3); xload(c + 4); sched_fence(zero); }
          }
        }
        WG_WAIT(0);
        wfree(6);
        pin<112>(acc);
        const uint32_t hbar = bars + 8 * (B_HFULL + 8 * tile);
        const uint32_t hrem = mapa(sb + OFF_H + wt * 16, r ^ 1), brem = mapa(hbar, r ^ 1);
        float th[2][16];
        auto tanhs = [&](int i0, int i1) {
#pragma unroll
          for (int i = i0; i < i1; i++) if (i < 112) asm("tanh.approx.f32 %0, %1;" : "=f"(th[(i >> 4) & 1][i & 15]) : "f"(acc[i]));
        };
        tanhs(0, 16);
        pin<16>(th[0]);
        mbar_wait(bars + 8 * (B_HFREE + tile), layer);
#pragma unroll
        for (int bk = 0; bk < 9; bk++) {
          if (bk >= 2) {
            const int pc = bk - 2;
            mbar_wait(hbar + 8 * pc, layer);
            lds128(h[14 + 2 * pc], sb + OFF_H + (2 * pc) * 2048 + wt * 16);
            lds128(h[15 + 2 * pc], sb + OFF_H + (2 * pc + 1) * 2048 + wt * 16);
          } else if (bk > 0) {
            sched_fence(zero);
          }
          if (bk < 7) {
            tanhs(16 * bk + 16, 16 * bk + 32);
#pragma unroll
            for (int s = 2 * bk; s < 2 * bk + 2; s++) {
#pragma unroll
              for (int k = 0; k < 4; k++) {
                const int i = 8 * s + 2 * k;
                h[s][k] = pack2(fmaf(acc[i], th[bk & 1][i & 15], acc[i]), fmaf(acc[i + 1], th[bk & 1][(i + 1) & 15], acc[i + 1]));
              }
              st_async128(hrem + s * 2048, h[s][0], h[s][1], h[s][2], h[s][3], brem + 8 * bk);
            }
            if (bk < 6) pin<16>(th[(bk + 1) & 1]);
          }
        }
        if (layer == 0 && wt < 7) mbar_expect(hbar + 8 * wt, 4096);
      }
      __syncwarp();
      if (lane == 0) {
        if (tile) mbar_arrive(bars + 8 * B_HCONS);
        else mbar_arrive_remote(mapa(bars + 8 * (B_HFREE + 1), r ^ 1));
      }
      {
        uint4* pp = g_P + ((((gi * 2 + tile) * 8 + 2 * w + (lane >> 4)) * 4 + ps) * 448 + r * 224 + (lane & 15));
        float acc[2][32];
        const uint64_t om = mkdesc(sb + 4096 * r, 0, HI_128, zero), ot = mkdesc(sb + 24576 * (1 - r), 0, HI_128, zero);
        const uint64_t pm = mkdesc(sb + 4096 * (1 - r), 0, HI_128, zero), pt = mkdesc(sb + 24576 * r, 0, HI_128, zero);
        const uint64_t om2 = mkdesc(sb + 2048 * r, 0, HI_64, zero), ot2 = mkdesc(sb + 12288 * (1 - r), 0, HI_64, zero);
        const uint64_t pm2 = mkdesc(sb + 2048 * (1 - r), 0, HI_64, zero), pt2 = mkdesc(sb + 12288 * r, 0, HI_64, zero);
        auto mma = [&](int q, int s) {
          const int half = s >= 14, k = s - 14 * half, kk = k < 12 ? k : k - 12;
          if (q > 0) wg_mma<64, 1>(acc[q & 1], h[s], (k < 12 ? (half ? pm : om) : (half ? pt : ot)) + (((2 * q - 1 + half) * SLOT + kk * 2048) >> 4), s == 0);
          else wg_mma<32, 1>(acc[0], h[s], (k < 12 ? (half ? pm2 : om2) : (half ? pt2 : ot2)) + ((half * 14336 + kk * 1024) >> 4), s == 0);
        };
        auto put = [&](int q, int c) {
          if (q == 0 && c > 1) return;
          float* a = acc[q & 1] + 8 * c;
          pin<8>(a);
          ll_st(pp + (4 * ((q + 3) & 3) + c) * 16, tagged(bmul2(pack2(a[0], a[1]), P_DOWN2), tag), pack2(a[2], a[3]), pack2(a[4], a[5]), pack2(a[6], a[7]));
        };
        wfull2(0, 1);
        turn_wait(2 + wg);
#pragma unroll
        for (int q = 0; q < 4; q++) {
          WG_FENCE();
#pragma unroll
          for (int sg = 0; sg < 7; sg++) {
#pragma unroll
            for (int s = 4 * sg; s < 4 * sg + 4; s++) mma(q, s);
            WG_COMMIT();
            if (q == 3 && sg == 6) break;
            if (q > 0) {
              WG_WAIT(2);
              if (sg == 1) wfree(2 * q - 2);
              if (sg == 5) wfree(2 * q - 1);
              if (sg == 1) put(q - 1, 0);
              if (sg >= 3 && sg <= 5) put(q - 1, sg - 2);
              if (q == 3 && sg == 3) pload(praw, 12, 16);
              if (q == 3 && sg == 5) pload(praw, 0, 4);
              if (sg == 2) { wfull(2 * q, 1); WG_FENCE(); }
              else if (sg >= 1 && sg <= (q == 1 ? 3 : 5)) { sched_fence(zero); WG_FENCE(); }
            }
          }
          if (q == 1 || q == 2) wfull(2 * q + 1, 1);
        }
        if (!(tile & layer)) turn_give(3 - wg);
        WG_WAIT(0);
        wfree(6);
        put(3, 0); put(3, 1); put(3, 2); put(3, 3);
      }
      if (layer == 1) break;
      reduce(IntC<0>(), praw, tag);
    }
    reduce(IntC<1>(), praw, mktag(2 * epoch + 1));
    if (tid == 128) g_epoch[blockIdx.x] = (epoch + 1) % 3;
  }
}

typedef CUresult (*EncodeFn)(CUtensorMap*, CUtensorMapDataType, cuuint32_t, void*, const cuuint64_t*, const cuuint64_t*,
                             const cuuint32_t*, const cuuint32_t*, CUtensorMapInterleave, CUtensorMapSwizzle,
                             CUtensorMapL2promotion, CUtensorMapFloatOOBfill);

static void encode(EncodeFn fn, CUtensorMap* m, const void* base, int rank, const cuuint64_t* dims, const cuuint64_t* strides,
            const cuuint32_t* box, CUtensorMapSwizzle sw, CUtensorMapL2promotion pr) {
  const cuuint32_t es[3] = {1, 1, 1};
  fn(m, CU_TENSOR_MAP_DATA_TYPE_BFLOAT16, rank, const_cast<void*>(base), dims, strides, box, es,
     CU_TENSOR_MAP_INTERLEAVE_NONE, sw, pr, CU_TENSOR_MAP_FLOAT_OOB_FILL_NONE);
}


extern "C" void kernel_launch(void* const* d_in, const int* in_sizes, int n_in, void* d_out, int out_size) {
  const __nv_bfloat16* q = (const __nv_bfloat16*)d_in[0];
  const __nv_bfloat16* k = (const __nv_bfloat16*)d_in[1];
  const __nv_bfloat16* v = (const __nv_bfloat16*)d_in[2];
  const __nv_bfloat16* shiftk = (const __nv_bfloat16*)d_in[3];
  const __nv_bfloat16* ssmk = (const __nv_bfloat16*)d_in[4];
  const __nv_bfloat16* ssmD = (const __nv_bfloat16*)d_in[5];
  const __nv_bfloat16* w1 = (const __nv_bfloat16*)d_in[7];
  const __nv_bfloat16* w2 = (const __nv_bfloat16*)d_in[8];

  EncodeFn fn = nullptr;
  cudaDriverEntryPointQueryResult qr;
  cudaGetDriverEntryPoint("cuTensorMapEncodeTiled", (void**)&fn, cudaEnableDefault, &qr);
  cudaFuncSetAttribute(h3ffn_kernel, cudaFuncAttributeMaxDynamicSharedMemorySize, SMEM_TOTAL);

  CUtensorMap tmK, tmV, tmW1m, tmW1t, tmW2m, tmW2t;
  {
    const cuuint64_t dims[3] = {D_, S_ / 4, 4}, str[2] = {D_ * 8, D_ * 2};
    const cuuint32_t box[3] = {8, 33, 4};
    encode(fn, &tmK, k, 3, dims, str, box, CU_TENSOR_MAP_SWIZZLE_NONE, CU_TENSOR_MAP_L2_PROMOTION_L2_128B);
    encode(fn, &tmV, v, 3, dims, str, box, CU_TENSOR_MAP_SWIZZLE_NONE, CU_TENSOR_MAP_L2_PROMOTION_L2_128B);
  }
  {
    const cuuint64_t dims[3] = {64, D_, F_ / 64}, str[2] = {F_ * 2, 128};
    const cuuint32_t box[3] = {64, 32, 3};
    encode(fn, &tmW1m, w1, 3, dims, str, box, CU_TENSOR_MAP_SWIZZLE_128B, CU_TENSOR_MAP_L2_PROMOTION_NONE);
  }
  {
    const cuuint64_t dims[2] = {F_, D_}, str[1] = {F_ * 2};
    const cuuint32_t box[2] = {32, 32};
    encode(fn, &tmW1t, w1, 2, dims, str, box, CU_TENSOR_MAP_SWIZZLE_64B, CU_TENSOR_MAP_L2_PROMOTION_NONE);
  }
  {
    const cuuint64_t dims[2] = {D_, F_}, str[1] = {D_ * 2};
    const cuuint32_t boxm[2] = {64, 224}, boxt[2] = {32, 224};
    encode(fn, &tmW2m, w2, 2, dims, str, boxm, CU_TENSOR_MAP_SWIZZLE_128B, CU_TENSOR_MAP_L2_PROMOTION_NONE);
    encode(fn, &tmW2t, w2, 2, dims, str, boxt, CU_TENSOR_MAP_SWIZZLE_64B, CU_TENSOR_MAP_L2_PROMOTION_NONE);
  }
  void *pY, *pX, *pP, *pE;
  cudaGetSymbolAddress(&pY, dg_Y);
  cudaGetSymbolAddress(&pX, dg_X);
  cudaGetSymbolAddress(&pP, dg_P);
  cudaGetSymbolAddress(&pE, dg_epoch);
  h3ffn_kernel<<<128, NTHREADS, SMEM_TOTAL>>>(ssmk, ssmD, shiftk, (unsigned*)pE, k, v, 0u, (uint4*)pY, (uint4*)pX, (uint4*)pP, q, w1, w2,
                                              (__nv_bfloat16*)d_out, tmK, tmV, tmW1m, tmW1t, tmW2m, tmW2t);
}
```
